```python
import torch

def _softmax(x, axis=-1):
    return torch.softmax(x, dim=axis)
def _gelu(x):
    return torch.nn.functional.gelu(x, approximate="tanh")
def _silu(x):
    return torch.nn.functional.silu(x)
def _sigmoid(x):
    return torch.sigmoid(x)
def _layernorm(x, axis=-1, eps=1e-5):
    m = x.mean(dim=axis, keepdim=True)
    v = x.var(dim=axis, keepdim=True, unbiased=False)
    return (x - m) / torch.sqrt(v + eps)
def _scatter_add(tgt, idx, src, axis=0):
    return tgt.clone().index_add_(axis, idx, src)
def _segment_sum(src, seg, n):
    out = torch.zeros((n,) + src.shape[1:], dtype=src.dtype)
    return out.index_add_(0, seg, src)
def _pad(x, pw):
    flat = tuple(v for pair in reversed(pw) for v in pair)
    return torch.nn.functional.pad(x, flat)

kernel_name = 'concat_heads__gqa_block_cached__gqa_block_cached__near_ridge'

def setup_inputs():

    _w = (lambda a: (lambda t: t.to(torch.bfloat16) if t.is_floating_point() else t)(torch.as_tensor(a)))
    def _A_setup():
        B, Sq, D = 16, 48, 640
        Hq, Hkv, Sk, Dh = 32, 32, 48, 192
        assert Hq % Hkv == 0, (Hq, Hkv)
        return {
            "x": _w((lambda *s: torch.randn(*s, dtype=torch.bfloat16) * 0.8)(B, Sq, D)),
            "k_cache": _w((lambda *s: torch.randn(*s, dtype=torch.bfloat16) * 0.8)(B, Hkv, Sk, Dh)),
            "v_cache": _w((lambda *s: torch.randn(*s, dtype=torch.bfloat16) * 0.05)(B, Hkv, Sk, Dh)),
            "wq": _w((lambda *s: torch.randn(*s, dtype=torch.bfloat16) * 0.8)(D, Hq * Dh) * (D ** -0.5)),
            "wo": _w((lambda *s: torch.randn(*s, dtype=torch.bfloat16) * 0.05)(Hq * Dh, D) * ((Hq * Dh) ** -0.5)),
        }
    _A_in = _A_setup()

    def _B_setup():
        B, Sq, D = 16, 48, 640
        Hq, Hkv, Sk, Dh = 32, 32, 48, 192
        assert Hq % Hkv == 0, (Hq, Hkv)
        return {
            "x": _w((lambda *s: torch.randn(*s, dtype=torch.bfloat16) * 0.8)(B, Sq, D)),
            "k_cache": _w((lambda *s: torch.randn(*s, dtype=torch.bfloat16) * 0.8)(B, Hkv, Sk, Dh)),
            "v_cache": _w((lambda *s: torch.randn(*s, dtype=torch.bfloat16) * 0.05)(B, Hkv, Sk, Dh)),
            "wq": _w((lambda *s: torch.randn(*s, dtype=torch.bfloat16) * 0.8)(D, Hq * Dh) * (D ** -0.5)),
            "wo": _w((lambda *s: torch.randn(*s, dtype=torch.bfloat16) * 0.05)(Hq * Dh, D) * ((Hq * Dh) ** -0.5)),
        }
    _B_in = _B_setup()

    return {
        "A_x": _A_in["x"],
        "A_k_cache": _A_in["k_cache"],
        "A_v_cache": _A_in["v_cache"],
        "A_wq": _A_in["wq"],
        "A_wo": _A_in["wo"],
        "B_x": _B_in["x"],
        "B_k_cache": _B_in["k_cache"],
        "B_v_cache": _B_in["v_cache"],
        "B_wq": _B_in["wq"],
        "B_wo": _B_in["wo"],
    }

def reference(A_x, A_k_cache, A_v_cache, A_wq, A_wo, B_x, B_k_cache, B_v_cache, B_wq, B_wo):
    def _A_ref(x, k_cache, v_cache, wq, wo):
        B, Sq, D = x.shape
        Hq, Dh = 32, 192
        Hkv = k_cache.shape[1]
        rep = Hq // Hkv
        q = (lambda x, *d: x.permute(*d))((x @ wq).reshape(B, Sq, Hq, Dh), 0, 2, 1, 3)
        k = (lambda x, n, axis: torch.repeat_interleave(x, n, dim=axis))(k_cache, rep, axis=1)
        v = (lambda x, n, axis: torch.repeat_interleave(x, n, dim=axis))(v_cache, rep, axis=1)
        scores = torch.einsum("bhqd,bhkd->bhqk", q, k) * (Dh ** -0.5)
        p = _softmax(scores, axis=-1)
        o = torch.einsum("bhqk,bhkd->bhqd", p, v)
        return (lambda x, *d: x.permute(*d))(o, 0, 2, 1, 3).reshape(B, Sq, Hq * Dh) @ wo

    def _B_ref(x, k_cache, v_cache, wq, wo):
        B, Sq, D = x.shape
        Hq, Dh = 32, 192
        Hkv = k_cache.shape[1]
        rep = Hq // Hkv
        q = (lambda x, *d: x.permute(*d))((x @ wq).reshape(B, Sq, Hq, Dh), 0, 2, 1, 3)
        k = (lambda x, n, axis: torch.repeat_interleave(x, n, dim=axis))(k_cache, rep, axis=1)
        v = (lambda x, n, axis: torch.repeat_interleave(x, n, dim=axis))(v_cache, rep, axis=1)
        scores = torch.einsum("bhqd,bhkd->bhqk", q, k) * (Dh ** -0.5)
        p = _softmax(scores, axis=-1)
        o = torch.einsum("bhqk,bhkd->bhqd", p, v)
        return (lambda x, *d: x.permute(*d))(o, 0, 2, 1, 3).reshape(B, Sq, Hq * Dh) @ wo

    a = _A_ref(A_x, A_k_cache, A_v_cache, A_wq, A_wo)
    b = _B_ref(B_x, B_k_cache, B_v_cache, B_wq, B_wo)
    return torch.concatenate([a, b], axis=-1)
```

```cpp
#include <cuda_runtime.h>
#include <cuda_bf16.h>
#include <cuda.h>
#include <stdint.h>

#define EXCHANGE 1
#define PF_DIST 0
#define SPIN_LIMIT (1u << 27)

namespace fk {

constexpr int SLOT_BYTES = 24576;
constexpr int NSLOT = 9;
constexpr int NSLOT_O = 5;
constexpr int XBUF_BYTES = 16384;
constexpr int XBUF_OFF = NSLOT_O * SLOT_BYTES;
constexpr int BAR_OFF = NSLOT * SLOT_BYTES;
constexpr int SMEM_BYTES = BAR_OFF + 512 + 1024;
constexpr int NITEMS = 72;
constexpr int NTHREADS = 512;
constexpr unsigned ARRIVALS = EXCHANGE ? 8u : 16u;

struct Params {
  CUtensorMap x[2], wq[2], k[2], v[2], wo[2];
};

__device__ float g_scratch[2 * 4 * 10 * 3 * 4096];
__device__ unsigned int g_counter[2 * 4 * 10 * 3];
#define TSTAMP(i)

__device__ __forceinline__ uint32_t smem_u32(const void* p) { return (uint32_t)__cvta_generic_to_shared(p); }
__device__ __forceinline__ void mbar_init(uint32_t bar, uint32_t cnt) {
  asm volatile("mbarrier.init.shared::cta.b64 [%0], %1;" ::"r"(bar), "r"(cnt) : "memory");
}
__device__ __forceinline__ void mbar_expect_tx(uint32_t bar, uint32_t bytes) {
  asm volatile("mbarrier.arrive.expect_tx.shared::cta.b64 _, [%0], %1;" ::"r"(bar), "r"(bytes) : "memory");
}
__device__ __forceinline__ uint32_t mapa(uint32_t addr, uint32_t cta) {
  uint32_t r;
  asm volatile("mapa.shared::cluster.u32 %0, %1, %2;" : "=r"(r) : "r"(addr), "r"(cta));
  return r;
}
__device__ __forceinline__ void mbar_arrive_cluster(uint32_t remote_bar) {
  asm volatile("mbarrier.arrive.shared::cluster.b64 _, [%0];" ::"r"(remote_bar) : "memory");
}
__device__ __forceinline__ uint32_t mbar_try(uint32_t bar, uint32_t parity) {
  uint32_t ok;
  asm volatile("{\n.reg .pred p;\nmbarrier.try_wait.parity.shared::cta.b64 p, [%1], %2;\nselp.u32 %0, 1, 0, p;\n}\n"
               : "=r"(ok) : "r"(bar), "r"(parity) : "memory");
  return ok;
}
__device__ __forceinline__ uint32_t mbar_try_cluster(uint32_t bar, uint32_t parity) {
  uint32_t ok;
  asm volatile("{\n.reg .pred p;\nmbarrier.try_wait.parity.acquire.cluster.shared::cta.b64 p, [%1], %2;\nselp.u32 %0, 1, 0, p;\n}\n"
               : "=r"(ok) : "r"(bar), "r"(parity) : "memory");
  return ok;
}
__device__ __forceinline__ uint32_t clk32() {
  uint32_t t;
  asm volatile("mov.u32 %0, %%clock;" : "=r"(t));
  return t;
}
__device__ __forceinline__ void mbar_wait(uint32_t bar, uint32_t parity) {
  if (mbar_try(bar, parity)) return;
  const uint32_t t0 = clk32();
  while (!mbar_try(bar, parity)) {
    if (clk32() - t0 > SPIN_LIMIT) break;
  }
}
__device__ __forceinline__ void mbar_wait_cluster(uint32_t bar, uint32_t parity) {
  if (mbar_try_cluster(bar, parity)) return;
  const uint32_t t0 = clk32();
  while (!mbar_try_cluster(bar, parity)) {
    if (clk32() - t0 > SPIN_LIMIT) break;
  }
}
__device__ __forceinline__ void cluster_sync() {
  asm volatile("barrier.cluster.arrive.release.aligned;\nbarrier.cluster.wait.acquire.aligned;\n" ::: "memory");
}
__device__ __forceinline__ void tma2d(uint32_t dst, const CUtensorMap* m, int c0, int c1, uint32_t bar) {
  asm volatile("cp.async.bulk.tensor.2d.shared::cluster.global.mbarrier::complete_tx::bytes [%0], [%1, {%3, %4}], [%2];"
               ::"r"(dst), "l"(m), "r"(bar), "r"(c0), "r"(c1) : "memory");
}
__device__ __forceinline__ void tma2d_mc(uint32_t dst, const CUtensorMap* m, int c0, int c1, uint32_t bar, uint16_t mask) {
  asm volatile("cp.async.bulk.tensor.2d.shared::cluster.global.mbarrier::complete_tx::bytes.multicast::cluster [%0], [%1, {%3, %4}], [%2], %5;"
               ::"r"(dst), "l"(m), "r"(bar), "r"(c0), "r"(c1), "h"(mask) : "memory");
}
__device__ __forceinline__ void tma3d(uint32_t dst, const CUtensorMap* m, int c0, int c1, int c2, uint32_t bar) {
  asm volatile("cp.async.bulk.tensor.3d.shared::cluster.global.mbarrier::complete_tx::bytes [%0], [%1, {%3, %4, %5}], [%2];"
               ::"r"(dst), "l"(m), "r"(bar), "r"(c0), "r"(c1), "r"(c2) : "memory");
}
__device__ __forceinline__ void tma4d(uint32_t dst, const CUtensorMap* m, int c0, int c1, int c2, int c3, uint32_t bar) {
  asm volatile("cp.async.bulk.tensor.4d.shared::cluster.global.mbarrier::complete_tx::bytes [%0], [%1, {%3, %4, %5, %6}], [%2];"
               ::"r"(dst), "l"(m), "r"(bar), "r"(c0), "r"(c1), "r"(c2), "r"(c3) : "memory");
}
__device__ __forceinline__ void pf2d(const CUtensorMap* m, int c0, int c1) {
  asm volatile("cp.async.bulk.prefetch.tensor.2d.L2.global [%0, {%1, %2}];" ::"l"(m), "r"(c0), "r"(c1) : "memory");
}
__device__ __forceinline__ void pf3d(const CUtensorMap* m, int c0, int c1, int c2) {
  asm volatile("cp.async.bulk.prefetch.tensor.3d.L2.global [%0, {%1, %2, %3}];" ::"l"(m), "r"(c0), "r"(c1), "r"(c2) : "memory");
}
__device__ __forceinline__ void pf4d(const CUtensorMap* m, int c0, int c1, int c2, int c3) {
  asm volatile("cp.async.bulk.prefetch.tensor.4d.L2.global [%0, {%1, %2, %3, %4}];" ::"l"(m), "r"(c0), "r"(c1), "r"(c2), "r"(c3) : "memory");
}
__device__ __forceinline__ void wg_fence() { asm volatile("wgmma.fence.sync.aligned;" ::: "memory"); }
__device__ __forceinline__ void wg_commit() { asm volatile("wgmma.commit_group.sync.aligned;" ::: "memory"); }
template <int N> __device__ __forceinline__ void wg_wait() { asm volatile("wgmma.wait_group.sync.aligned %0;" ::"n"(N) : "memory"); }
template <int N> __device__ __forceinline__ void fence_regs(float (&d)[N]) {
#pragma unroll
  for (int i = 0; i < N; i++) asm volatile("" : "+f"(d[i])::"memory");
}
template <int N> __device__ __forceinline__ void fence_regs(uint32_t (&d)[N]) {
#pragma unroll
  for (int i = 0; i < N; i++) asm volatile("" : "+r"(d[i])::"memory");
}
template <int N> __device__ __forceinline__ void pin_regs(const uint32_t* d, uint32_t never, uint32_t addr) {
#pragma unroll
  for (int i = 0; i < N; i += 4)
    asm volatile("{\n.reg .pred p;\nsetp.ne.u32 p, %5, 0;\n@p st.shared.v4.b32 [%0], {%1, %2, %3, %4};\n}\n"
                 ::"r"(addr), "r"(d[i]), "r"(d[i + 1]), "r"(d[i + 2]), "r"(d[i + 3]), "r"(never) : "memory");
}
__device__ __forceinline__ uint32_t pack_bf16(float lo, float hi) {
  uint32_t r;
  asm("cvt.rn.bf16x2.f32 %0, %1, %2;" : "=r"(r) : "f"(hi), "f"(lo));
  return r;
}
__device__ __forceinline__ uint64_t make_desc(uint32_t addr, uint32_t lbo, uint32_t sbo) {
  return (uint64_t)((addr & 0x3FFFFu) >> 4) | ((uint64_t)(lbo >> 4) << 16) | ((uint64_t)(sbo >> 4) << 32) | (1ull << 62);
}

__device__ __forceinline__ void wgmma_n192_ss_tb(float (&d)[96], uint64_t da, uint64_t db, int scale_d) {
  asm volatile("{\n.reg .pred p;\nsetp.ne.b32 p, %98, 0;\n"
    "wgmma.mma_async.sync.aligned.m64n192k16.f32.bf16.bf16 "
    "{%0, %1, %2, %3, %4, %5, %6, %7, %8, %9, %10, %11, %12, %13, %14, %15, %16, %17, %18, %19, %20, %21, %22, %23, %24, %25, %26, %27, %28, %29, %30, %31, %32, %33, %34, %35, %36, %37, %38, %39, %40, %41, %42, %43, %44, %45, %46, %47, %48, %49, %50, %51, %52, %53, %54, %55, %56, %57, %58, %59, %60, %61, %62, %63, %64, %65, %66, %67, %68, %69, %70, %71, %72, %73, %74, %75, %76, %77, %78, %79, %80, %81, %82, %83, %84, %85, %86, %87, %88, %89, %90, %91, %92, %93, %94, %95}, "
    "%96, %97, p, 1, 1, 0, 1;\n}\n"
    : "+f"(d[0]), "+f"(d[1]), "+f"(d[2]), "+f"(d[3]), "+f"(d[4]), "+f"(d[5]), "+f"(d[6]), "+f"(d[7]), "+f"(d[8]), "+f"(d[9]), "+f"(d[10]), "+f"(d[11]), "+f"(d[12]), "+f"(d[13]), "+f"(d[14]), "+f"(d[15]), "+f"(d[16]), "+f"(d[17]), "+f"(d[18]), "+f"(d[19]), "+f"(d[20]), "+f"(d[21]), "+f"(d[22]), "+f"(d[23]), "+f"(d[24]), "+f"(d[25]), "+f"(d[26]), "+f"(d[27]), "+f"(d[28]), "+f"(d[29]), "+f"(d[30]), "+f"(d[31]), "+f"(d[32]), "+f"(d[33]), "+f"(d[34]), "+f"(d[35]), "+f"(d[36]), "+f"(d[37]), "+f"(d[38]), "+f"(d[39]), "+f"(d[40]), "+f"(d[41]), "+f"(d[42]), "+f"(d[43]), "+f"(d[44]), "+f"(d[45]), "+f"(d[46]), "+f"(d[47]), "+f"(d[48]), "+f"(d[49]), "+f"(d[50]), "+f"(d[51]), "+f"(d[52]), "+f"(d[53]), "+f"(d[54]), "+f"(d[55]), "+f"(d[56]), "+f"(d[57]), "+f"(d[58]), "+f"(d[59]), "+f"(d[60]), "+f"(d[61]), "+f"(d[62]), "+f"(d[63]), "+f"(d[64]), "+f"(d[65]), "+f"(d[66]), "+f"(d[67]), "+f"(d[68]), "+f"(d[69]), "+f"(d[70]), "+f"(d[71]), "+f"(d[72]), "+f"(d[73]), "+f"(d[74]), "+f"(d[75]), "+f"(d[76]), "+f"(d[77]), "+f"(d[78]), "+f"(d[79]), "+f"(d[80]), "+f"(d[81]), "+f"(d[82]), "+f"(d[83]), "+f"(d[84]), "+f"(d[85]), "+f"(d[86]), "+f"(d[87]), "+f"(d[88]), "+f"(d[89]), "+f"(d[90]), "+f"(d[91]), "+f"(d[92]), "+f"(d[93]), "+f"(d[94]), "+f"(d[95])
    : "l"(da), "l"(db), "r"(scale_d));
}
__device__ __forceinline__ void wgmma_n96_rs(float (&d)[48], uint32_t a0, uint32_t a1, uint32_t a2, uint32_t a3, uint64_t db, int scale_d) {
  asm volatile("{\n.reg .pred p;\nsetp.ne.b32 p, %53, 0;\n"
    "wgmma.mma_async.sync.aligned.m64n96k16.f32.bf16.bf16 "
    "{%0, %1, %2, %3, %4, %5, %6, %7, %8, %9, %10, %11, %12, %13, %14, %15, %16, %17, %18, %19, %20, %21, %22, %23, %24, %25, %26, %27, %28, %29, %30, %31, %32, %33, %34, %35, %36, %37, %38, %39, %40, %41, %42, %43, %44, %45, %46, %47}, "
    "{%48, %49, %50, %51}, %52, p, 1, 1, 0;\n}\n"
    : "+f"(d[0]), "+f"(d[1]), "+f"(d[2]), "+f"(d[3]), "+f"(d[4]), "+f"(d[5]), "+f"(d[6]), "+f"(d[7]), "+f"(d[8]), "+f"(d[9]), "+f"(d[10]), "+f"(d[11]), "+f"(d[12]), "+f"(d[13]), "+f"(d[14]), "+f"(d[15]), "+f"(d[16]), "+f"(d[17]), "+f"(d[18]), "+f"(d[19]), "+f"(d[20]), "+f"(d[21]), "+f"(d[22]), "+f"(d[23]), "+f"(d[24]), "+f"(d[25]), "+f"(d[26]), "+f"(d[27]), "+f"(d[28]), "+f"(d[29]), "+f"(d[30]), "+f"(d[31]), "+f"(d[32]), "+f"(d[33]), "+f"(d[34]), "+f"(d[35]), "+f"(d[36]), "+f"(d[37]), "+f"(d[38]), "+f"(d[39]), "+f"(d[40]), "+f"(d[41]), "+f"(d[42]), "+f"(d[43]), "+f"(d[44]), "+f"(d[45]), "+f"(d[46]), "+f"(d[47])
    : "r"(a0), "r"(a1), "r"(a2), "r"(a3), "l"(db), "r"(scale_d));
}
__device__ __forceinline__ void wgmma_n64_rs_tb(float (&d)[32], uint32_t a0, uint32_t a1, uint32_t a2, uint32_t a3, uint64_t db, int scale_d) {
  asm volatile("{\n.reg .pred p;\nsetp.ne.b32 p, %37, 0;\n"
    "wgmma.mma_async.sync.aligned.m64n64k16.f32.bf16.bf16 "
    "{%0, %1, %2, %3, %4, %5, %6, %7, %8, %9, %10, %11, %12, %13, %14, %15, %16, %17, %18, %19, %20, %21, %22, %23, %24, %25, %26, %27, %28, %29, %30, %31}, "
    "{%32, %33, %34, %35}, %36, p, 1, 1, 1;\n}\n"
    : "+f"(d[0]), "+f"(d[1]), "+f"(d[2]), "+f"(d[3]), "+f"(d[4]), "+f"(d[5]), "+f"(d[6]), "+f"(d[7]), "+f"(d[8]), "+f"(d[9]), "+f"(d[10]), "+f"(d[11]), "+f"(d[12]), "+f"(d[13]), "+f"(d[14]), "+f"(d[15]), "+f"(d[16]), "+f"(d[17]), "+f"(d[18]), "+f"(d[19]), "+f"(d[20]), "+f"(d[21]), "+f"(d[22]), "+f"(d[23]), "+f"(d[24]), "+f"(d[25]), "+f"(d[26]), "+f"(d[27]), "+f"(d[28]), "+f"(d[29]), "+f"(d[30]), "+f"(d[31])
    : "r"(a0), "r"(a1), "r"(a2), "r"(a3), "l"(db), "r"(scale_d));
}

__device__ __forceinline__ int chunk_of(int t, int r, int rot) {
  int u = (t >> 1) + rot;
  if (u >= 5) u -= 5;
  return 2 * u + ((t & 1) ? r : 1 - r);
}

template <bool PF>
__device__ __forceinline__ void do_item(const Params& P, int i, int p, int tg, int h0, int r, int rot, uint32_t dst, uint32_t bar) {
  if (i < 52) {
    const int hh = i >= 26;
    const int j = i - 26 * hh;
    const int h = h0 + hh;
    if (j < 20) {
      const int kc = j >> 1;
      if (!(j & 1)) {
        if (PF) pf2d(&P.x[p], kc * 64, tg * 192 + r * 96);
        else tma2d_mc(dst + r * 12288, &P.x[p], kc * 64, tg * 192 + r * 96, bar, (uint16_t)3);
      } else {
        if (PF) pf3d(&P.wq[p], 0, kc * 64, h * 3);
        else tma3d(dst, &P.wq[p], 0, kc * 64, h * 3, bar);
      }
    } else if (j < 23) {
      if (PF) pf4d(&P.k[p], (j - 20) * 64, 0, h, tg * 4);
      else tma4d(dst, &P.k[p], (j - 20) * 64, 0, h, tg * 4, bar);
    } else {
      if (PF) pf4d(&P.v[p], (j - 23) * 64, 0, h, tg * 4);
      else tma4d(dst, &P.v[p], (j - 23) * 64, 0, h, tg * 4, bar);
    }
  } else {
    const int j = i - 52;
    const int c = chunk_of(j >> 1, r, rot);
    const int h = h0 + (j & 1);
    if (PF) pf2d(&P.wo[p], c * 64, h * 192);
    else tma2d(dst, &P.wo[p], c * 64, h * 192, bar);
  }
}

struct Ring {
  uint32_t slot, phase;
  template <int N> __device__ __forceinline__ void advance() {
    if (++slot == N) { slot = 0; phase ^= 1; }
  }
};

__device__ __forceinline__ void do_head(uint32_t (&o)[48], Ring& rg, uint32_t sbase, uint32_t full0, uint32_t rel0,
                                        int w, int lane, int hf, int tbase, uint32_t never) {
  auto release = [&](uint32_t s) { if (lane < 2) mbar_arrive_cluster(rel0 + 8 * s); };
  uint32_t qf[48];
  {
    float acc[96];
    uint32_t psx, psw;
    {
      const uint32_t sx = rg.slot, px = rg.phase; rg.advance<NSLOT>();
      const uint32_t sw = rg.slot, pw = rg.phase; rg.advance<NSLOT>();
      mbar_wait(full0 + 8 * sx, px);
      mbar_wait(full0 + 8 * sw, pw);
      const uint64_t da = make_desc(sbase + sx * SLOT_BYTES + w * 8192, 16, 1024);
      const uint64_t db = make_desc(sbase + sw * SLOT_BYTES, 8192, 1024);
      wg_fence();
#pragma unroll
      for (int s = 0; s < 4; s++) wgmma_n192_ss_tb(acc, da + 2 * s, db + 128 * s, s != 0);
      wg_commit();
      psx = sx; psw = sw;
    }
#pragma unroll 1
    for (int kc = 1; kc < 10; kc++) {
      const uint32_t sx = rg.slot, px = rg.phase; rg.advance<NSLOT>();
      const uint32_t sw = rg.slot, pw = rg.phase; rg.advance<NSLOT>();
      mbar_wait(full0 + 8 * sx, px);
      mbar_wait(full0 + 8 * sw, pw);
      const uint64_t da = make_desc(sbase + sx * SLOT_BYTES + w * 8192, 16, 1024);
      const uint64_t db = make_desc(sbase + sw * SLOT_BYTES, 8192, 1024);
      wg_fence();
#pragma unroll
      for (int s = 0; s < 4; s++) wgmma_n192_ss_tb(acc, da + 2 * s, db + 128 * s, 1);
      wg_commit();
      wg_wait<1>(); release(psx); release(psw);
      psx = sx; psw = sw;
    }
    wg_wait<0>();
    fence_regs(acc);
    release(psx); release(psw);
#pragma unroll
    for (int i = 24; i < 48; i++) qf[i] = pack_bf16(acc[2 * i], acc[2 * i + 1]);
    pin_regs<24>(qf + 24, never, full0);
#pragma unroll
    for (int i = 0; i < 24; i++) qf[i] = pack_bf16(acc[2 * i], acc[2 * i + 1]);
    pin_regs<24>(qf, never, full0);
  }
  TSTAMP(tbase + 0);
  uint32_t pa[24];
  {
    float sacc[48];
    uint32_t ks[3];
    fence_regs(qf);
#pragma unroll
    for (int dc = 0; dc < 3; dc++) {
      ks[dc] = rg.slot;
      mbar_wait(full0 + 8 * rg.slot, rg.phase);
      rg.advance<NSLOT>();
      const uint64_t db = make_desc(sbase + ks[dc] * SLOT_BYTES + w * 6144, 16, 1024);
      wg_fence();
#pragma unroll
      for (int s = 0; s < 4; s++) {
        const int j = dc * 4 + s;
        wgmma_n96_rs(sacc, qf[4 * j], qf[4 * j + 1], qf[4 * j + 2], qf[4 * j + 3], db + 2 * s, j != 0);
      }
    }
    wg_commit();
    wg_wait<0>();
    fence_regs(sacc);
    release(ks[0]); release(ks[1]); release(ks[2]);
    float v[24];
#pragma unroll
    for (int i = 0; i < 24; i++) v[i] = hf ? sacc[24 + i] : sacc[i];
    float m0 = v[0], m1 = v[2];
#pragma unroll
    for (int t = 0; t < 6; t++) {
      m0 = fmaxf(m0, fmaxf(v[4 * t], v[4 * t + 1]));
      m1 = fmaxf(m1, fmaxf(v[4 * t + 2], v[4 * t + 3]));
    }
    m0 = fmaxf(m0, __shfl_xor_sync(0xffffffffu, m0, 1));
    m1 = fmaxf(m1, __shfl_xor_sync(0xffffffffu, m1, 1));
    m0 = fmaxf(m0, __shfl_xor_sync(0xffffffffu, m0, 2));
    m1 = fmaxf(m1, __shfl_xor_sync(0xffffffffu, m1, 2));
    const float cs = 0.07216878364870322f * 1.4426950408889634f;
    const float b0 = m0 * cs, b1 = m1 * cs;
    float s0 = 0.f, s1 = 0.f;
#pragma unroll
    for (int t = 0; t < 6; t++) {
      v[4 * t] = exp2f(fmaf(v[4 * t], cs, -b0));
      v[4 * t + 1] = exp2f(fmaf(v[4 * t + 1], cs, -b0));
      v[4 * t + 2] = exp2f(fmaf(v[4 * t + 2], cs, -b1));
      v[4 * t + 3] = exp2f(fmaf(v[4 * t + 3], cs, -b1));
      s0 += v[4 * t] + v[4 * t + 1];
      s1 += v[4 * t + 2] + v[4 * t + 3];
    }
    s0 += __shfl_xor_sync(0xffffffffu, s0, 1);
    s1 += __shfl_xor_sync(0xffffffffu, s1, 1);
    s0 += __shfl_xor_sync(0xffffffffu, s0, 2);
    s1 += __shfl_xor_sync(0xffffffffu, s1, 2);
    const float r0 = 1.0f / s0, r1 = 1.0f / s1;
#pragma unroll
    for (int t = 0; t < 6; t++) {
      const uint32_t lo = pack_bf16(v[4 * t] * r0, v[4 * t + 1] * r0);
      const uint32_t hi = pack_bf16(v[4 * t + 2] * r1, v[4 * t + 3] * r1);
      pa[2 * t] = hf ? 0u : lo;
      pa[2 * t + 1] = hf ? 0u : hi;
      pa[12 + 2 * t] = hf ? lo : 0u;
      pa[12 + 2 * t + 1] = hf ? hi : 0u;
    }
  }
  TSTAMP(tbase + 1);
  {
    fence_regs(pa);
    float oa[32], ob[32];
    const uint32_t s0 = rg.slot, p0 = rg.phase; rg.advance<NSLOT>();
    const uint32_t s1 = rg.slot, p1 = rg.phase; rg.advance<NSLOT>();
    const uint32_t s2 = rg.slot, p2 = rg.phase; rg.advance<NSLOT>();
    mbar_wait(full0 + 8 * s0, p0);
    {
      const uint64_t db = make_desc(sbase + s0 * SLOT_BYTES + w * 6144, 16, 1024);
      wg_fence();
#pragma unroll
      for (int j = 0; j < 6; j++) wgmma_n64_rs_tb(oa, pa[4 * j], pa[4 * j + 1], pa[4 * j + 2], pa[4 * j + 3], db + 128 * j, j != 0);
    }
    mbar_wait(full0 + 8 * s1, p1);
    {
      const uint64_t db = make_desc(sbase + s1 * SLOT_BYTES + w * 6144, 16, 1024);
      wg_fence();
#pragma unroll
      for (int j = 0; j < 6; j++) wgmma_n64_rs_tb(ob, pa[4 * j], pa[4 * j + 1], pa[4 * j + 2], pa[4 * j + 3], db + 128 * j, j != 0);
    }
    wg_commit();
    wg_wait<0>();
    fence_regs(oa); fence_regs(ob);
    release(s0); release(s1);
#pragma unroll
    for (int i = 0; i < 16; i++) o[i] = pack_bf16(oa[2 * i], oa[2 * i + 1]);
    pin_regs<16>(o, never, full0);
#pragma unroll
    for (int i = 0; i < 16; i++) o[16 + i] = pack_bf16(ob[2 * i], ob[2 * i + 1]);
    pin_regs<16>(o + 16, never, full0);
    float oc[32];
    mbar_wait(full0 + 8 * s2, p2);
    {
      const uint64_t db = make_desc(sbase + s2 * SLOT_BYTES + w * 6144, 16, 1024);
      wg_fence();
#pragma unroll
      for (int j = 0; j < 6; j++) wgmma_n64_rs_tb(oc, pa[4 * j], pa[4 * j + 1], pa[4 * j + 2], pa[4 * j + 3], db + 128 * j, j != 0);
    }
    wg_commit();
    wg_wait<0>();
    fence_regs(oc);
    release(s2);
#pragma unroll
    for (int i = 0; i < 16; i++) o[32 + i] = pack_bf16(oc[2 * i], oc[2 * i + 1]);
    pin_regs<16>(o + 32, never, full0);
  }
  TSTAMP(tbase + 2);
}

__device__ __forceinline__ void oproj_chunk(float (&a)[32], const uint32_t (&o0)[48], const uint32_t (&o1)[48], Ring& rg,
                                            uint32_t sbase, uint32_t full0, uint32_t rel0, int lane, int accumulate) {
  const uint32_t s0 = rg.slot, p0 = rg.phase; rg.advance<NSLOT_O>();
  const uint32_t s1 = rg.slot, p1 = rg.phase; rg.advance<NSLOT_O>();
  mbar_wait(full0 + 8 * s0, p0);
  {
    const uint64_t db = make_desc(sbase + s0 * SLOT_BYTES, 16, 1024);
    wg_fence();
#pragma unroll
    for (int j = 0; j < 12; j++)
      wgmma_n64_rs_tb(a, o0[4 * j], o0[4 * j + 1], o0[4 * j + 2], o0[4 * j + 3], db + 128 * j, j == 0 ? accumulate : 1);
    wg_commit();
  }
  mbar_wait(full0 + 8 * s1, p1);
  {
    const uint64_t db = make_desc(sbase + s1 * SLOT_BYTES, 16, 1024);
    wg_fence();
#pragma unroll
    for (int j = 0; j < 12; j++)
      wgmma_n64_rs_tb(a, o1[4 * j], o1[4 * j + 1], o1[4 * j + 2], o1[4 * j + 3], db + 128 * j, 1);
    wg_commit();
  }
  wg_wait<1>();
  if (lane < 2) mbar_arrive_cluster(rel0 + 8 * s0);
  wg_wait<0>();
  fence_regs(a);
  if (lane < 2) mbar_arrive_cluster(rel0 + 8 * s1);
}

__global__ void __cluster_dims__(2, 1, 1) __launch_bounds__(NTHREADS, 1)
fused_kernel(const __grid_constant__ Params P, __nv_bfloat16* __restrict__ out) {
  extern __shared__ uint8_t smem_raw[];
  const uint32_t sbase = (smem_u32(smem_raw) + 1023u) & ~1023u;
  const uint32_t full0 = sbase + BAR_OFF;
  const uint32_t empty0 = full0 + 72;
  const uint32_t xfull0 = full0 + 144;
  const uint32_t xempty0 = full0 + 192;
  const uint32_t flag0 = full0 + 256;

  const int tid = threadIdx.x, lane = tid & 31;
  const int warp = __shfl_sync(0xffffffffu, tid >> 5, 0);
  const int bid = blockIdx.x;
  const int hp = bid & 15, tg = (bid >> 4) & 3, p = bid >> 6;
  const int r = hp & 1;
  const int h0 = hp * 2;
  const int rot = (hp >> 1) % 5;

  if (tid == 0) {
    for (int i = 0; i < NSLOT; i++) { mbar_init(full0 + 8 * i, 1); mbar_init(empty0 + 8 * i, 24); }
    for (int i = 0; i < 6; i++) { mbar_init(xfull0 + 8 * i, 1); mbar_init(xempty0 + 8 * i, 1); }
    asm volatile("fence.mbarrier_init.release.cluster;" ::: "memory");
  }
  __syncthreads();
  cluster_sync();

  if (warp >= 12) {
    asm volatile("setmaxnreg.dec.sync.aligned.u32 32;");
    if (warp == 12 && lane == 0) {
      uint32_t slot = 0, phase = 0;
#pragma unroll 1
      for (int i = 0; i < NITEMS; i++) {
        if (i == 52) { slot = 0; phase = 0; }
        mbar_wait(empty0 + 8 * slot, phase ^ 1);
        mbar_expect_tx(full0 + 8 * slot, SLOT_BYTES);
        do_item<false>(P, i, p, tg, h0, r, rot, sbase + slot * SLOT_BYTES, full0 + 8 * slot);
        if (++slot == (i < 52 ? NSLOT : NSLOT_O)) { slot = 0; phase ^= 1; }
      }
    }
    __syncwarp();
    cluster_sync();
  } else {
    asm volatile("setmaxnreg.inc.sync.aligned.u32 160;");
    const int w = warp >> 2;
    const int wt = tid & 127;
    const int hf = warp / 3 - w;
    const uint32_t rel0 = mapa(empty0, lane & 1);
    Ring rg{0, 0};
    TSTAMP(0);
    uint32_t o0[48], o1[48];
    const uint32_t never = (out == nullptr);
    do_head(o0, rg, sbase, full0, rel0, w, lane, hf, 1, never);
    do_head(o1, rg, sbase, full0, rel0, w, lane, hf, 4, never);
#pragma unroll
    for (int i = 0; i < 12; i++) o0[i] ^= never;
    fence_regs(o0); fence_regs(o1);

    rg.slot = 0; rg.phase = 0;
    const int grp = p * 4 + tg;
    unsigned mask = 0;
    unsigned pend_old = 0; int pend_c = -1;
    int prev_c = -1;
    constexpr int NOWN = EXCHANGE ? 5 : 10;
#pragma unroll 1
    for (int u = 0; u < NOWN; u++) {
      const int b = u & 1;
      const uint32_t xb = sbase + XBUF_OFF + (b * 3 + w) * XBUF_BYTES + wt * 16;
      float a[32];
      oproj_chunk(a, o0, o1, rg, sbase, full0, rel0, lane, 0);
      if (u == 0) {
        mbar_wait(empty0 + 8 * 5, 1); mbar_wait(empty0 + 8 * 6, 1);
        mbar_wait(empty0 + 8 * 7, 0); mbar_wait(empty0 + 8 * 8, 0);
      }
      if (u >= 2) mbar_wait_cluster(xempty0 + 8 * (b * 3 + w), ((u >> 1) - 1) & 1);
      {
        const uint32_t rxb = mapa(xb, r ^ 1);
        const uint32_t rbar = mapa(xfull0 + 8 * (b * 3 + w), r ^ 1);
#pragma unroll
        for (int j = 0; j < 8; j++)
          asm volatile("st.async.weak.shared::cluster.mbarrier::complete_tx::bytes.v4.f32 [%0], {%1, %2, %3, %4}, [%5];"
                       ::"r"(rxb + j * 2048), "f"(a[4 * j]), "f"(a[4 * j + 1]), "f"(a[4 * j + 2]), "f"(a[4 * j + 3]), "r"(rbar) : "memory");
      }
      if (wt == 0) mbar_expect_tx(xfull0 + 8 * (b * 3 + w), XBUF_BYTES);
      mbar_wait_cluster(xfull0 + 8 * (b * 3 + w), (u >> 1) & 1);
#pragma unroll
      for (int j = 0; j < 8; j++)
        asm volatile("ld.shared.v4.f32 {%0, %1, %2, %3}, [%4];"
                     : "=f"(a[4 * j]), "=f"(a[4 * j + 1]), "=f"(a[4 * j + 2]), "=f"(a[4 * j + 3]) : "r"(xb + j * 2048) : "memory");
      oproj_chunk(a, o0, o1, rg, sbase, full0, rel0, lane, 1);
      const int c = chunk_of(2 * u + 1, r, rot);
#pragma unroll
      for (int j = 0; j < 8; j++)
        asm volatile("st.shared.v4.f32 [%0], {%1, %2, %3, %4};"
                     ::"r"(xb + j * 2048), "f"(a[4 * j]), "f"(a[4 * j + 1]), "f"(a[4 * j + 2]), "f"(a[4 * j + 3]) : "memory");
      asm volatile("fence.proxy.async.shared::cta;" ::: "memory");
      if (wt == 0 && prev_c >= 0) {
        asm volatile("cp.async.bulk.wait_group 0;" ::: "memory");
        mbar_arrive_cluster(mapa(xempty0 + 8 * ((b ^ 1) * 3 + w), r ^ 1));
        if (pend_c >= 0 && pend_old == ARRIVALS - 1) mask |= 1u << pend_c;
        __threadfence();
        pend_old = atomicAdd(&g_counter[(grp * 10 + prev_c) * 3 + w], 1u);
        pend_c = prev_c;
      }
      asm volatile("bar.sync %0, 128;" ::"r"(1 + w) : "memory");
      if (wt == 0) {
        float* dst = g_scratch + (size_t)((grp * 10 + c) * 3 + w) * 4096;
        asm volatile("cp.reduce.async.bulk.global.shared::cta.bulk_group.add.f32 [%0], [%1], %2;"
                     ::"l"(dst), "r"(xb), "r"(XBUF_BYTES) : "memory");
        asm volatile("cp.async.bulk.commit_group;" ::: "memory");
      }
      prev_c = c;
    }
    TSTAMP(7);
    if (wt == 0) {
      asm volatile("cp.async.bulk.wait_group 0;" ::: "memory");
      if (pend_c >= 0 && pend_old == ARRIVALS - 1) mask |= 1u << pend_c;
      __threadfence();
      const unsigned old = atomicAdd(&g_counter[(grp * 10 + prev_c) * 3 + w], 1u);
      if (old == ARRIVALS - 1) mask |= 1u << prev_c;
      __threadfence();
      asm volatile("st.shared.u32 [%0], %1;" ::"r"(flag0 + 4 * w), "r"(mask) : "memory");
    }
    asm volatile("bar.sync %0, 128;" ::"r"(1 + w) : "memory");
    asm volatile("ld.shared.u32 %0, [%1];" : "=r"(mask) : "r"(flag0 + 4 * w) : "memory");
    TSTAMP(8);
    while (mask) {
      const int c = __ffs(mask) - 1;
      mask &= mask - 1;
      float* src = g_scratch + (size_t)((grp * 10 + c) * 3 + w) * 4096;
#pragma unroll
      for (int rep = 0; rep < 2; rep++) {
        const int idx = wt + 128 * rep;
        const int j = idx & 7, g = (idx >> 3) & 7, wb = idx >> 6;
        float4* s4 = reinterpret_cast<float4*>(src) + (j * 128 + wb * 32 + g * 4);
        const float4 f0 = __ldcg(s4), f1 = __ldcg(s4 + 1), f2 = __ldcg(s4 + 2), f3 = __ldcg(s4 + 3);
        const int row = tg * 192 + w * 64 + wb * 16 + g;
        __nv_bfloat16* d0 = out + (size_t)row * 1280 + p * 640 + c * 64 + j * 8;
        uint4 lo, hi;
        lo.x = pack_bf16(f0.x, f0.y); lo.y = pack_bf16(f1.x, f1.y); lo.z = pack_bf16(f2.x, f2.y); lo.w = pack_bf16(f3.x, f3.y);
        hi.x = pack_bf16(f0.z, f0.w); hi.y = pack_bf16(f1.z, f1.w); hi.z = pack_bf16(f2.z, f2.w); hi.w = pack_bf16(f3.z, f3.w);
        *reinterpret_cast<uint4*>(d0) = lo;
        *reinterpret_cast<uint4*>(d0 + 8 * 1280) = hi;
        const float4 z = make_float4(0.f, 0.f, 0.f, 0.f);
        __stcg(s4, z); __stcg(s4 + 1, z); __stcg(s4 + 2, z); __stcg(s4 + 3, z);
      }
      if (wt == 0) g_counter[(grp * 10 + c) * 3 + w] = 0u;
    }
    TSTAMP(9);
    cluster_sync();
  }
}

typedef CUresult (*EncodeFn)(CUtensorMap*, CUtensorMapDataType, cuuint32_t, void*, const cuuint64_t*, const cuuint64_t*,
                             const cuuint32_t*, const cuuint32_t*, CUtensorMapInterleave, CUtensorMapSwizzle,
                             CUtensorMapL2promotion, CUtensorMapFloatOOBfill);

static void encode(EncodeFn fn, CUtensorMap* m, const void* ptr, int rank, const cuuint64_t* dims, const cuuint64_t* strides,
                   const cuuint32_t* box) {
  cuuint32_t es[5] = {1, 1, 1, 1, 1};
  fn(m, CU_TENSOR_MAP_DATA_TYPE_BFLOAT16, (cuuint32_t)rank, const_cast<void*>(ptr), dims, strides, box, es,
     CU_TENSOR_MAP_INTERLEAVE_NONE, CU_TENSOR_MAP_SWIZZLE_128B, CU_TENSOR_MAP_L2_PROMOTION_L2_256B,
     CU_TENSOR_MAP_FLOAT_OOB_FILL_NONE);
}

}

extern "C" void kernel_launch(void* const* d_in, const int* in_sizes, int n_in, void* d_out, int out_size) {
  using namespace fk;
  static Params params;
  static const void* cached[10] = {nullptr};
  static EncodeFn fn = nullptr;
  if (!fn) {
    void* f = nullptr;
    cudaDriverEntryPointQueryResult st;
    cudaGetDriverEntryPoint("cuTensorMapEncodeTiled", &f, cudaEnableDefault, &st);
    fn = (EncodeFn)f;
    cudaFuncSetAttribute(fused_kernel, cudaFuncAttributeMaxDynamicSharedMemorySize, SMEM_BYTES);
  }
  bool same = true;
  for (int i = 0; i < 10; i++) same = same && (cached[i] == d_in[i]);
  if (!same) {
    for (int p = 0; p < 2; p++) {
      const void* x = d_in[5 * p + 0];
      const void* k = d_in[5 * p + 1];
      const void* v = d_in[5 * p + 2];
      const void* wq = d_in[5 * p + 3];
      const void* wo = d_in[5 * p + 4];
      {
        cuuint64_t d[2] = {640, 768}, s[1] = {1280};
        cuuint32_t b[2] = {64, 96};
        encode(fn, &params.x[p], x, 2, d, s, b);
      }
      {
        cuuint64_t d[3] = {64, 640, 96}, s[2] = {12288, 128};
        cuuint32_t b[3] = {64, 64, 3};
        encode(fn, &params.wq[p], wq, 3, d, s, b);
      }
      {
        cuuint64_t d[4] = {192, 48, 32, 16}, s[3] = {384, 18432, 589824};
        cuuint32_t b[4] = {64, 48, 1, 4};
        encode(fn, &params.k[p], k, 4, d, s, b);
        encode(fn, &params.v[p], v, 4, d, s, b);
      }
      {
        cuuint64_t d[2] = {640, 6144}, s[1] = {1280};
        cuuint32_t b[2] = {64, 192};
        encode(fn, &params.wo[p], wo, 2, d, s, b);
      }
    }
    for (int i = 0; i < 10; i++) cached[i] = d_in[i];
  }
  fused_kernel<<<128, NTHREADS, SMEM_BYTES>>>(params, (__nv_bfloat16*)d_out);
}
```

```cpp
#include <cuda_runtime.h>
#include <cuda_bf16.h>
#include <cuda.h>
#include <stdint.h>

#define PF_ON 1
#define PF_T0 1500
#define PF_DT1 1400
#define PF_N1 4
#define PF_DT2 1000
#define TOKEN 1
#define TOKEN_AT 8
#define FENCE_MODE 1
#define SPIN_LIMIT (1u << 27)

namespace fk {

constexpr int SLOT_BYTES = 24576;
constexpr int NSLOT = 9;
constexpr int NSLOT_O = 8;
constexpr int XBUF_BYTES = 8192;
constexpr int XBUF_OFF = NSLOT_O * SLOT_BYTES;
constexpr int BAR_OFF = NSLOT * SLOT_BYTES;
constexpr int SMEM_BYTES = BAR_OFF + 1024 + 1024;
constexpr int NTHREADS = 512;

struct Params {
  CUtensorMap x[2], wq[2], k[2], v[2], wo[2];
  const char* kp[2]; const char* vp[2]; const char* wqp[2]; const char* wop[2];
};

__device__ uint4 g_part[8 * 10 * 4 * (SLOT_BYTES / 16)];
__device__ unsigned int g_flag[8 * 10 * 4];
__device__ uint4 g_late[8 * 10 * 3 * (SLOT_BYTES / 16)];
#define TSTAMP(i)
#define HSTAMP(i)
#define GSTAMP(a, b)
#define HSTAMP2(i)
#define CSTAMP(i)
#define TDUMP()

__device__ __forceinline__ uint32_t smem_u32(const void* p) { return (uint32_t)__cvta_generic_to_shared(p); }
__device__ __forceinline__ void mbar_init(uint32_t bar, uint32_t cnt) {
  asm volatile("mbarrier.init.shared::cta.b64 [%0], %1;" ::"r"(bar), "r"(cnt) : "memory");
}
__device__ __forceinline__ void mbar_expect_tx(uint32_t bar, uint32_t bytes) {
  asm volatile("mbarrier.arrive.expect_tx.shared::cta.b64 _, [%0], %1;" ::"r"(bar), "r"(bytes) : "memory");
}
__device__ __forceinline__ uint32_t mapa(uint32_t addr, uint32_t cta) {
  uint32_t r;
  asm volatile("mapa.shared::cluster.u32 %0, %1, %2;" : "=r"(r) : "r"(addr), "r"(cta));
  return r;
}
__device__ __forceinline__ void mbar_arrive_cluster(uint32_t remote_bar) {
  asm volatile("mbarrier.arrive.shared::cluster.b64 _, [%0];" ::"r"(remote_bar) : "memory");
}
__device__ __forceinline__ uint32_t mbar_try(uint32_t bar, uint32_t parity) {
  uint32_t ok;
  asm volatile("{\n.reg .pred p;\nmbarrier.try_wait.parity.shared::cta.b64 p, [%1], %2;\nselp.u32 %0, 1, 0, p;\n}\n"
               : "=r"(ok) : "r"(bar), "r"(parity) : "memory");
  return ok;
}
__device__ __forceinline__ uint32_t mbar_test(uint32_t bar, uint32_t parity) {
  uint32_t ok;
  asm volatile("{\n.reg .pred p;\nmbarrier.test_wait.parity.shared::cta.b64 p, [%1], %2;\nselp.u32 %0, 1, 0, p;\n}\n"
               : "=r"(ok) : "r"(bar), "r"(parity) : "memory");
  return ok;
}
__device__ __forceinline__ uint32_t mbar_try_cluster(uint32_t bar, uint32_t parity) {
  uint32_t ok;
  asm volatile("{\n.reg .pred p;\nmbarrier.try_wait.parity.acquire.cluster.shared::cta.b64 p, [%1], %2;\nselp.u32 %0, 1, 0, p;\n}\n"
               : "=r"(ok) : "r"(bar), "r"(parity) : "memory");
  return ok;
}
__device__ __forceinline__ uint32_t clk32() {
  uint32_t t;
  asm volatile("mov.u32 %0, %%clock;" : "=r"(t));
  return t;
}
#define DBGREC(a, b)
__device__ __forceinline__ void mbar_wait(uint32_t bar, uint32_t parity) {
  if (mbar_try(bar, parity)) return;
  const uint32_t t0 = clk32();
  while (!mbar_try(bar, parity)) {
    if (clk32() - t0 > SPIN_LIMIT) { DBGREC(bar, parity); break; }
  }
}
__device__ __forceinline__ void mbar_wait_cluster(uint32_t bar, uint32_t parity) {
  if (mbar_try_cluster(bar, parity)) return;
  const uint32_t t0 = clk32();
  while (!mbar_try_cluster(bar, parity)) {
    if (clk32() - t0 > SPIN_LIMIT) break;
  }
}
__device__ __forceinline__ void cluster_sync() {
  asm volatile("barrier.cluster.arrive.release.aligned;\nbarrier.cluster.wait.acquire.aligned;\n" ::: "memory");
}
__device__ __forceinline__ void tma2d(uint32_t dst, const CUtensorMap* m, int c0, int c1, uint32_t bar) {
  asm volatile("cp.async.bulk.tensor.2d.shared::cluster.global.mbarrier::complete_tx::bytes [%0], [%1, {%3, %4}], [%2];"
               ::"r"(dst), "l"(m), "r"(bar), "r"(c0), "r"(c1) : "memory");
}
__device__ __forceinline__ void tma2d_mc(uint32_t dst, const CUtensorMap* m, int c0, int c1, uint32_t bar, uint16_t mask) {
  asm volatile("cp.async.bulk.tensor.2d.shared::cluster.global.mbarrier::complete_tx::bytes.multicast::cluster [%0], [%1, {%3, %4}], [%2], %5;"
               ::"r"(dst), "l"(m), "r"(bar), "r"(c0), "r"(c1), "h"(mask) : "memory");
}
__device__ __forceinline__ void tma3d(uint32_t dst, const CUtensorMap* m, int c0, int c1, int c2, uint32_t bar) {
  asm volatile("cp.async.bulk.tensor.3d.shared::cluster.global.mbarrier::complete_tx::bytes [%0], [%1, {%3, %4, %5}], [%2];"
               ::"r"(dst), "l"(m), "r"(bar), "r"(c0), "r"(c1), "r"(c2) : "memory");
}
__device__ __forceinline__ void tma4d(uint32_t dst, const CUtensorMap* m, int c0, int c1, int c2, int c3, uint32_t bar) {
  asm volatile("cp.async.bulk.tensor.4d.shared::cluster.global.mbarrier::complete_tx::bytes [%0], [%1, {%3, %4, %5, %6}], [%2];"
               ::"r"(dst), "l"(m), "r"(bar), "r"(c0), "r"(c1), "r"(c2), "r"(c3) : "memory");
}
__device__ __forceinline__ void mbar_arrive(uint32_t bar) {
  asm volatile("mbarrier.arrive.shared::cta.b64 _, [%0];" ::"r"(bar) : "memory");
}
__device__ __forceinline__ uint32_t touch_l2(const void* p) {
  uint32_t v;
  asm volatile("ld.global.cg.L2::128B.b32 %0, [%1];" : "=r"(v) : "l"(p));
  return v;
}
__device__ __forceinline__ unsigned ld_acquire(const unsigned* p) {
  unsigned v;
  asm volatile("ld.acquire.gpu.global.u32 %0, [%1];" : "=r"(v) : "l"(p) : "memory");
  return v;
}
__device__ __forceinline__ void wg_fence() { asm volatile("wgmma.fence.sync.aligned;" ::: "memory"); }
__device__ __forceinline__ void wg_commit() { asm volatile("wgmma.commit_group.sync.aligned;" ::: "memory"); }
template <int N> __device__ __forceinline__ void wg_wait() { asm volatile("wgmma.wait_group.sync.aligned %0;" ::"n"(N) : "memory"); }
template <int N> __device__ __forceinline__ void fence_regs(float (&d)[N]) {
#pragma unroll
  for (int i = 0; i < N; i++) asm volatile("" : "+f"(d[i])::"memory");
}
template <int N> __device__ __forceinline__ void fence_regs(uint32_t (&d)[N]) {
#pragma unroll
  for (int i = 0; i < N; i++) asm volatile("" : "+r"(d[i])::"memory");
}
template <int N> __device__ __forceinline__ void pin_regs(const uint32_t* d, uint32_t never, uint32_t addr) {
#pragma unroll
  for (int i = 0; i < N; i += 4)
    asm volatile("{\n.reg .pred p;\nsetp.ne.u32 p, %5, 0;\n@p st.shared.v4.b32 [%0], {%1, %2, %3, %4};\n}\n"
                 ::"r"(addr), "r"(d[i]), "r"(d[i + 1]), "r"(d[i + 2]), "r"(d[i + 3]), "r"(never) : "memory");
}
__device__ __forceinline__ uint32_t pack_bf16(float lo, float hi) {
  uint32_t r;
  asm("cvt.rn.bf16x2.f32 %0, %1, %2;" : "=r"(r) : "f"(hi), "f"(lo));
  return r;
}
__device__ __forceinline__ uint64_t make_desc(uint32_t addr, uint32_t lbo, uint32_t sbo) {
  return (uint64_t)((addr & 0x3FFFFu) >> 4) | ((uint64_t)(lbo >> 4) << 16) | ((uint64_t)(sbo >> 4) << 32) | (1ull << 62);
}

__device__ __forceinline__ void wgmma_n192_ss_tb(float (&d)[96], uint64_t da, uint64_t db, int scale_d) {
  asm volatile("{\n.reg .pred p;\nsetp.ne.b32 p, %98, 0;\n"
    "wgmma.mma_async.sync.aligned.m64n192k16.f32.bf16.bf16 "
    "{%0, %1, %2, %3, %4, %5, %6, %7, %8, %9, %10, %11, %12, %13, %14, %15, %16, %17, %18, %19, %20, %21, %22, %23, %24, %25, %26, %27, %28, %29, %30, %31, %32, %33, %34, %35, %36, %37, %38, %39, %40, %41, %42, %43, %44, %45, %46, %47, %48, %49, %50, %51, %52, %53, %54, %55, %56, %57, %58, %59, %60, %61, %62, %63, %64, %65, %66, %67, %68, %69, %70, %71, %72, %73, %74, %75, %76, %77, %78, %79, %80, %81, %82, %83, %84, %85, %86, %87, %88, %89, %90, %91, %92, %93, %94, %95}, "
    "%96, %97, p, 1, 1, 0, 1;\n}\n"
    : "+f"(d[0]), "+f"(d[1]), "+f"(d[2]), "+f"(d[3]), "+f"(d[4]), "+f"(d[5]), "+f"(d[6]), "+f"(d[7]), "+f"(d[8]), "+f"(d[9]), "+f"(d[10]), "+f"(d[11]), "+f"(d[12]), "+f"(d[13]), "+f"(d[14]), "+f"(d[15]), "+f"(d[16]), "+f"(d[17]), "+f"(d[18]), "+f"(d[19]), "+f"(d[20]), "+f"(d[21]), "+f"(d[22]), "+f"(d[23]), "+f"(d[24]), "+f"(d[25]), "+f"(d[26]), "+f"(d[27]), "+f"(d[28]), "+f"(d[29]), "+f"(d[30]), "+f"(d[31]), "+f"(d[32]), "+f"(d[33]), "+f"(d[34]), "+f"(d[35]), "+f"(d[36]), "+f"(d[37]), "+f"(d[38]), "+f"(d[39]), "+f"(d[40]), "+f"(d[41]), "+f"(d[42]), "+f"(d[43]), "+f"(d[44]), "+f"(d[45]), "+f"(d[46]), "+f"(d[47]), "+f"(d[48]), "+f"(d[49]), "+f"(d[50]), "+f"(d[51]), "+f"(d[52]), "+f"(d[53]), "+f"(d[54]), "+f"(d[55]), "+f"(d[56]), "+f"(d[57]), "+f"(d[58]), "+f"(d[59]), "+f"(d[60]), "+f"(d[61]), "+f"(d[62]), "+f"(d[63]), "+f"(d[64]), "+f"(d[65]), "+f"(d[66]), "+f"(d[67]), "+f"(d[68]), "+f"(d[69]), "+f"(d[70]), "+f"(d[71]), "+f"(d[72]), "+f"(d[73]), "+f"(d[74]), "+f"(d[75]), "+f"(d[76]), "+f"(d[77]), "+f"(d[78]), "+f"(d[79]), "+f"(d[80]), "+f"(d[81]), "+f"(d[82]), "+f"(d[83]), "+f"(d[84]), "+f"(d[85]), "+f"(d[86]), "+f"(d[87]), "+f"(d[88]), "+f"(d[89]), "+f"(d[90]), "+f"(d[91]), "+f"(d[92]), "+f"(d[93]), "+f"(d[94]), "+f"(d[95])
    : "l"(da), "l"(db), "r"(scale_d));
}
__device__ __forceinline__ void wgmma_n96_rs(float (&d)[48], uint32_t a0, uint32_t a1, uint32_t a2, uint32_t a3, uint64_t db, int scale_d) {
  asm volatile("{\n.reg .pred p;\nsetp.ne.b32 p, %53, 0;\n"
    "wgmma.mma_async.sync.aligned.m64n96k16.f32.bf16.bf16 "
    "{%0, %1, %2, %3, %4, %5, %6, %7, %8, %9, %10, %11, %12, %13, %14, %15, %16, %17, %18, %19, %20, %21, %22, %23, %24, %25, %26, %27, %28, %29, %30, %31, %32, %33, %34, %35, %36, %37, %38, %39, %40, %41, %42, %43, %44, %45, %46, %47}, "
    "{%48, %49, %50, %51}, %52, p, 1, 1, 0;\n}\n"
    : "+f"(d[0]), "+f"(d[1]), "+f"(d[2]), "+f"(d[3]), "+f"(d[4]), "+f"(d[5]), "+f"(d[6]), "+f"(d[7]), "+f"(d[8]), "+f"(d[9]), "+f"(d[10]), "+f"(d[11]), "+f"(d[12]), "+f"(d[13]), "+f"(d[14]), "+f"(d[15]), "+f"(d[16]), "+f"(d[17]), "+f"(d[18]), "+f"(d[19]), "+f"(d[20]), "+f"(d[21]), "+f"(d[22]), "+f"(d[23]), "+f"(d[24]), "+f"(d[25]), "+f"(d[26]), "+f"(d[27]), "+f"(d[28]), "+f"(d[29]), "+f"(d[30]), "+f"(d[31]), "+f"(d[32]), "+f"(d[33]), "+f"(d[34]), "+f"(d[35]), "+f"(d[36]), "+f"(d[37]), "+f"(d[38]), "+f"(d[39]), "+f"(d[40]), "+f"(d[41]), "+f"(d[42]), "+f"(d[43]), "+f"(d[44]), "+f"(d[45]), "+f"(d[46]), "+f"(d[47])
    : "r"(a0), "r"(a1), "r"(a2), "r"(a3), "l"(db), "r"(scale_d));
}
__device__ __forceinline__ void wgmma_n64_rs_tb(float (&d)[32], uint32_t a0, uint32_t a1, uint32_t a2, uint32_t a3, uint64_t db, int scale_d) {
  asm volatile("{\n.reg .pred p;\nsetp.ne.b32 p, %37, 0;\n"
    "wgmma.mma_async.sync.aligned.m64n64k16.f32.bf16.bf16 "
    "{%0, %1, %2, %3, %4, %5, %6, %7, %8, %9, %10, %11, %12, %13, %14, %15, %16, %17, %18, %19, %20, %21, %22, %23, %24, %25, %26, %27, %28, %29, %30, %31}, "
    "{%32, %33, %34, %35}, %36, p, 1, 1, 1;\n}\n"
    : "+f"(d[0]), "+f"(d[1]), "+f"(d[2]), "+f"(d[3]), "+f"(d[4]), "+f"(d[5]), "+f"(d[6]), "+f"(d[7]), "+f"(d[8]), "+f"(d[9]), "+f"(d[10]), "+f"(d[11]), "+f"(d[12]), "+f"(d[13]), "+f"(d[14]), "+f"(d[15]), "+f"(d[16]), "+f"(d[17]), "+f"(d[18]), "+f"(d[19]), "+f"(d[20]), "+f"(d[21]), "+f"(d[22]), "+f"(d[23]), "+f"(d[24]), "+f"(d[25]), "+f"(d[26]), "+f"(d[27]), "+f"(d[28]), "+f"(d[29]), "+f"(d[30]), "+f"(d[31])
    : "r"(a0), "r"(a1), "r"(a2), "r"(a3), "l"(db), "r"(scale_d));
}

__device__ __forceinline__ int chunk_of(int i, int off) { const int c = i + off; return c >= 10 ? c - 10 : c; }
__device__ __forceinline__ int pos_of(int i, int c) { return i - (i > chunk_of(c, 6)) - (i > chunk_of(c, 1)); }
__device__ __forceinline__ int index_at(int t, int r, bool fin) { return (r == 0 && (t < 8 || fin)) ? (t ^ 1) : t; }

__device__ __forceinline__ void do_item(const Params& P, int i, int p, int tg, int h0, int r, uint32_t dst, uint32_t bar) {
  const int hh = i >= 26;
  const int j = i - 26 * hh;
  const int h = h0 + hh;
  if (j < 20) {
    const int kc = j >> 1;
    if (!(j & 1)) tma2d_mc(dst + r * 12288, &P.x[p], kc * 64, tg * 192 + r * 96, bar, (uint16_t)3);
    else tma3d(dst, &P.wq[p], 0, kc * 64, h * 3, bar);
  } else if (j < 23) {
    tma4d(dst, &P.k[p], (j - 20) * 64, 0, h, tg * 4, bar);
  } else {
    tma4d(dst, &P.v[p], (j - 23) * 64, 0, h, tg * 4, bar);
  }
}

__device__ __forceinline__ const char* pf_addr(const Params& P, int st, int l, int p, int tg, int hp, int off) {
  const int h0 = hp * 2;
  if (st < 29) {
    if (st >= 12 && st < 17) {
      const int idx = (st - 12) * 96 + l;
      const int k = (idx / 3) * 4 + tg;
      return P.wqp[p] + (size_t)k * 12288 + (h0 + 1) * 384 + (idx % 3) * 128;
    }
    const int hh = st >= 17;
    const int q = st - 17 * hh;
    const char* base = q < 6 ? P.kp[p] : P.vp[p];
    const int idx = (q < 6 ? q : q - 6) * 96 + l;
    const int bb = idx / 144;
    return base + ((size_t)((tg * 4 + bb) * 32 + h0 + hh) * 144 + (idx - bb * 144)) * 128;
  }
  return P.wop[p] + (size_t)(h0 * 192 + tg * 96 + l) * 1280 + chunk_of(st - 29, off) * 128;
}
constexpr int PF_STEPS = 33;

struct Ring {
  uint32_t slot, phase;
  template <int N> __device__ __forceinline__ void advance() {
    if (++slot == N) { slot = 0; phase ^= 1; }
  }
};

__device__ __forceinline__ void do_head(uint32_t (&o)[48], Ring& rg, uint32_t sbase, uint32_t full0, uint32_t rel0,
                                        int w, int lane, int hf, int tbase, uint32_t never) {
  auto release = [&](uint32_t s) { if (lane < 2) mbar_arrive_cluster(rel0 + 8 * s); };
  uint32_t qf[48];
  {
    float acc[96];
    uint32_t psx, psw;
    {
      const uint32_t sx = rg.slot, px = rg.phase; rg.advance<NSLOT>();
      const uint32_t sw = rg.slot, pw = rg.phase; rg.advance<NSLOT>();
      mbar_wait(full0 + 8 * sx, px);
      mbar_wait(full0 + 8 * sw, pw);
      const uint64_t da = make_desc(sbase + sx * SLOT_BYTES + w * 8192, 16, 1024);
      const uint64_t db = make_desc(sbase + sw * SLOT_BYTES, 8192, 1024);
      wg_fence();
#pragma unroll
      for (int s = 0; s < 4; s++) wgmma_n192_ss_tb(acc, da + 2 * s, db + 128 * s, s != 0);
      wg_commit();
      psx = sx; psw = sw;
    }
#pragma unroll 1
    for (int kc = 1; kc < 10; kc++) {
      const uint32_t sx = rg.slot, px = rg.phase; rg.advance<NSLOT>();
      const uint32_t sw = rg.slot, pw = rg.phase; rg.advance<NSLOT>();
      mbar_wait(full0 + 8 * sx, px);
      mbar_wait(full0 + 8 * sw, pw);
      const uint64_t da = make_desc(sbase + sx * SLOT_BYTES + w * 8192, 16, 1024);
      const uint64_t db = make_desc(sbase + sw * SLOT_BYTES, 8192, 1024);
      wg_fence();
#pragma unroll
      for (int s = 0; s < 4; s++) wgmma_n192_ss_tb(acc, da + 2 * s, db + 128 * s, 1);
      wg_commit();
      wg_wait<1>(); release(psx); release(psw);
      psx = sx; psw = sw;
    }
    wg_wait<0>();
    fence_regs(acc);
    release(psx); release(psw);
#pragma unroll
    for (int i = 24; i < 48; i++) qf[i] = pack_bf16(acc[2 * i], acc[2 * i + 1]);
    pin_regs<24>(qf + 24, never, full0);
#pragma unroll
    for (int i = 0; i < 24; i++) qf[i] = pack_bf16(acc[2 * i], acc[2 * i + 1]);
    pin_regs<24>(qf, never, full0);
  }
  TSTAMP(tbase + 0);
  uint32_t pa[24];
  {
    float sacc[48];
    uint32_t ks[3];
    fence_regs(qf);
#pragma unroll
    for (int dc = 0; dc < 3; dc++) {
      ks[dc] = rg.slot;
      mbar_wait(full0 + 8 * rg.slot, rg.phase);
      rg.advance<NSLOT>();
      const uint64_t db = make_desc(sbase + ks[dc] * SLOT_BYTES + w * 6144, 16, 1024);
      wg_fence();
#pragma unroll
      for (int s = 0; s < 4; s++) {
        const int j = dc * 4 + s;
        wgmma_n96_rs(sacc, qf[4 * j], qf[4 * j + 1], qf[4 * j + 2], qf[4 * j + 3], db + 2 * s, j != 0);
      }
    }
    wg_commit();
    wg_wait<0>();
    fence_regs(sacc);
    release(ks[0]); release(ks[1]); release(ks[2]);
    float v[24];
#pragma unroll
    for (int i = 0; i < 24; i++) v[i] = hf ? sacc[24 + i] : sacc[i];
    float m0 = v[0], m1 = v[2];
#pragma unroll
    for (int t = 0; t < 6; t++) {
      m0 = fmaxf(m0, fmaxf(v[4 * t], v[4 * t + 1]));
      m1 = fmaxf(m1, fmaxf(v[4 * t + 2], v[4 * t + 3]));
    }
    m0 = fmaxf(m0, __shfl_xor_sync(0xffffffffu, m0, 1));
    m1 = fmaxf(m1, __shfl_xor_sync(0xffffffffu, m1, 1));
    m0 = fmaxf(m0, __shfl_xor_sync(0xffffffffu, m0, 2));
    m1 = fmaxf(m1, __shfl_xor_sync(0xffffffffu, m1, 2));
    const float cs = 0.07216878364870322f * 1.4426950408889634f;
    const float b0 = m0 * cs, b1 = m1 * cs;
    float s0 = 0.f, s1 = 0.f;
#pragma unroll
    for (int t = 0; t < 6; t++) {
      v[4 * t] = exp2f(fmaf(v[4 * t], cs, -b0));
      v[4 * t + 1] = exp2f(fmaf(v[4 * t + 1], cs, -b0));
      v[4 * t + 2] = exp2f(fmaf(v[4 * t + 2], cs, -b1));
      v[4 * t + 3] = exp2f(fmaf(v[4 * t + 3], cs, -b1));
      s0 += v[4 * t] + v[4 * t + 1];
      s1 += v[4 * t + 2] + v[4 * t + 3];
    }
    s0 += __shfl_xor_sync(0xffffffffu, s0, 1);
    s1 += __shfl_xor_sync(0xffffffffu, s1, 1);
    s0 += __shfl_xor_sync(0xffffffffu, s0, 2);
    s1 += __shfl_xor_sync(0xffffffffu, s1, 2);
    const float r0 = 1.0f / s0, r1 = 1.0f / s1;
#pragma unroll
    for (int t = 0; t < 6; t++) {
      const uint32_t lo = pack_bf16(v[4 * t] * r0, v[4 * t + 1] * r0);
      const uint32_t hi = pack_bf16(v[4 * t + 2] * r1, v[4 * t + 3] * r1);
      pa[2 * t] = hf ? 0u : lo;
      pa[2 * t + 1] = hf ? 0u : hi;
      pa[12 + 2 * t] = hf ? lo : 0u;
      pa[12 + 2 * t + 1] = hf ? hi : 0u;
    }
  }
  TSTAMP(tbase + 1);
  {
    fence_regs(pa);
    float oa[32], ob[32];
    const uint32_t s0 = rg.slot, p0 = rg.phase; rg.advance<NSLOT>();
    const uint32_t s1 = rg.slot, p1 = rg.phase; rg.advance<NSLOT>();
    const uint32_t s2 = rg.slot, p2 = rg.phase; rg.advance<NSLOT>();
    mbar_wait(full0 + 8 * s0, p0);
    {
      const uint64_t db = make_desc(sbase + s0 * SLOT_BYTES + w * 6144, 16, 1024);
      wg_fence();
#pragma unroll
      for (int j = 0; j < 6; j++) wgmma_n64_rs_tb(oa, pa[4 * j], pa[4 * j + 1], pa[4 * j + 2], pa[4 * j + 3], db + 128 * j, j != 0);
    }
    mbar_wait(full0 + 8 * s1, p1);
    {
      const uint64_t db = make_desc(sbase + s1 * SLOT_BYTES + w * 6144, 16, 1024);
      wg_fence();
#pragma unroll
      for (int j = 0; j < 6; j++) wgmma_n64_rs_tb(ob, pa[4 * j], pa[4 * j + 1], pa[4 * j + 2], pa[4 * j + 3], db + 128 * j, j != 0);
    }
    wg_commit();
    wg_wait<0>();
    fence_regs(oa); fence_regs(ob);
    release(s0); release(s1);
#pragma unroll
    for (int i = 0; i < 16; i++) o[i] = pack_bf16(oa[2 * i], oa[2 * i + 1]);
    pin_regs<16>(o, never, full0);
#pragma unroll
    for (int i = 0; i < 16; i++) o[16 + i] = pack_bf16(ob[2 * i], ob[2 * i + 1]);
    pin_regs<16>(o + 16, never, full0);
    float oc[32];
    mbar_wait(full0 + 8 * s2, p2);
    {
      const uint64_t db = make_desc(sbase + s2 * SLOT_BYTES + w * 6144, 16, 1024);
      wg_fence();
#pragma unroll
      for (int j = 0; j < 6; j++) wgmma_n64_rs_tb(oc, pa[4 * j], pa[4 * j + 1], pa[4 * j + 2], pa[4 * j + 3], db + 128 * j, j != 0);
    }
    wg_commit();
    wg_wait<0>();
    fence_regs(oc);
    release(s2);
#pragma unroll
    for (int i = 0; i < 16; i++) o[32 + i] = pack_bf16(oc[2 * i], oc[2 * i + 1]);
    pin_regs<16>(o + 32, never, full0);
  }
  TSTAMP(tbase + 2);
}

__device__ __forceinline__ uint32_t oslot_addr(uint32_t sbase, uint32_t s) { return sbase + ((s + 7) & 7) * SLOT_BYTES; }
__device__ __forceinline__ void oproj_chunk(float (&a)[32], const uint32_t (&o0)[48], const uint32_t (&o1)[48], int t,
                                            uint32_t sbase, uint32_t fullo0, uint32_t emptyo0, int lane, int w, int wnext, bool pass) {
  const uint32_t s0 = (2 * t) & 7, s1 = s0 + 1, ph = (t >> 2) & 1;
  mbar_wait(fullo0 + 8 * s0, ph);
  mbar_wait(fullo0 + 8 * s1, ph);
  asm volatile("bar.sync %0, 256;" ::"r"(1 + w) : "memory");
  {
    const uint64_t db = make_desc(oslot_addr(sbase, s0), 16, 1024);
    wg_fence();
#pragma unroll
    for (int j = 0; j < 12; j++)
      wgmma_n64_rs_tb(a, o0[4 * j], o0[4 * j + 1], o0[4 * j + 2], o0[4 * j + 3], db + 128 * j, j != 0);
    wg_commit();
  }
  {
    const uint64_t db = make_desc(oslot_addr(sbase, s1), 16, 1024);
#pragma unroll
    for (int j = 0; j < 12; j++) {
      wgmma_n64_rs_tb(a, o1[4 * j], o1[4 * j + 1], o1[4 * j + 2], o1[4 * j + 3], db + 128 * j, 1);
      if (j == TOKEN_AT && pass) asm volatile("bar.arrive %0, 256;" ::"r"(1 + wnext) : "memory");
    }
    wg_commit();
  }
  wg_wait<1>();
  if (lane == 0) mbar_arrive(emptyo0 + 8 * s0);
  wg_wait<0>();
  fence_regs(a);
  if (lane == 0) mbar_arrive(emptyo0 + 8 * s1);
}

__device__ __forceinline__ void load_tile(uint32_t (&x)[16], uint32_t addr) {
#pragma unroll
  for (int j = 0; j < 4; j++)
    asm volatile("ld.shared.v4.b32 {%0, %1, %2, %3}, [%4];"
                 : "=r"(x[4 * j]), "=r"(x[4 * j + 1]), "=r"(x[4 * j + 2]), "=r"(x[4 * j + 3]) : "r"(addr + j * 2048) : "memory");
}
__device__ __forceinline__ void add_tile(float (&a)[32], const uint32_t (&x)[16]) {
#pragma unroll
  for (int j = 0; j < 16; j++) {
    a[2 * j] += __uint_as_float(x[j] << 16);
    a[2 * j + 1] += __uint_as_float(x[j] & 0xffff0000u);
  }
}

__global__ void __cluster_dims__(2, 1, 1) __launch_bounds__(NTHREADS, 1)
fused_kernel(const __grid_constant__ Params P, __nv_bfloat16* __restrict__ out) {
  extern __shared__ uint8_t smem_raw[];
  const uint32_t sbase = (smem_u32(smem_raw) + 1023u) & ~1023u;
  const uint32_t full0 = sbase + BAR_OFF;
  const uint32_t empty0 = full0 + 72;
  const uint32_t xfull0 = full0 + 144;
  const uint32_t xempty0 = full0 + 168;
  const uint32_t fullo0 = full0 + 192;
  const uint32_t emptyo0 = full0 + 256;
  const uint32_t rdone0 = full0 + 320;

  const int tid = threadIdx.x, lane = tid & 31;
  const int warp = __shfl_sync(0xffffffffu, tid >> 5, 0);
  const int bid = blockIdx.x;
  const int hp = bid & 15, tg = (bid >> 4) & 3, p = bid >> 6;
  const int r = hp & 1;
  const int h0 = hp * 2;
  const int grp = p * 4 + tg;
  const int off = (hp >> 1) + (hp >> 3);
  const bool fin = r == 1 || off == 0 || off == 5;

  if (tid == 384) {
    asm volatile("prefetch.tensormap [%0];" ::"l"(&P.wq[p]) : "memory");
    asm volatile("prefetch.tensormap [%0];" ::"l"(&P.x[p]) : "memory");
    for (int i = 0; i < NSLOT; i++) { mbar_init(full0 + 8 * i, 1); mbar_init(empty0 + 8 * i, 24); }
    for (int i = 0; i < 3; i++) { mbar_init(xfull0 + 8 * i, 1); mbar_init(xempty0 + 8 * i, 4); }
    for (int i = 0; i < 3; i++) mbar_init(rdone0 + 8 * i, 12);
    for (int i = 0; i < NSLOT_O; i++) { mbar_init(fullo0 + 8 * i, 1); mbar_init(emptyo0 + 8 * i, 12); }
    asm volatile("fence.mbarrier_init.release.cluster;" ::: "memory");
    for (int i = 0; i < NSLOT; i++) mbar_expect_tx(full0 + 8 * i, SLOT_BYTES);
    for (int i = 1; i < NSLOT; i += 2) do_item(P, i, p, tg, h0, r, sbase + i * SLOT_BYTES, full0 + 8 * i);
    for (int i = 0; i < 3; i++) mbar_expect_tx(xfull0 + 8 * i, XBUF_BYTES);
    asm volatile("prefetch.tensormap [%0];" ::"l"(&P.k[p]) : "memory");
    asm volatile("prefetch.tensormap [%0];" ::"l"(&P.v[p]) : "memory");
    asm volatile("prefetch.tensormap [%0];" ::"l"(&P.wo[p]) : "memory");
  }
  __syncwarp();
  asm volatile("barrier.cluster.arrive.relaxed.aligned;\nbarrier.cluster.wait.aligned;\n" ::: "memory");

  if (warp >= 12) {
    asm volatile("setmaxnreg.dec.sync.aligned.u32 32;");
    if (warp == 12) {
      if (lane == 0) {
        TSTAMP(0); CSTAMP(28);
#pragma unroll 1
        for (int i = 0; i < NSLOT; i += 2) do_item(P, i, p, tg, h0, r, sbase + i * SLOT_BYTES, full0 + 8 * i);
        uint32_t slot = 0, phase = 1;
#pragma unroll 1
        for (int i = NSLOT; i < 52; i++) {
          mbar_wait(empty0 + 8 * slot, phase ^ 1);
          mbar_expect_tx(full0 + 8 * slot, SLOT_BYTES);
          do_item(P, i, p, tg, h0, r, sbase + slot * SLOT_BYTES, full0 + 8 * slot);
          if (++slot == NSLOT) { slot = 0; phase ^= 1; }
        }
        TSTAMP(2); CSTAMP(29);
#pragma unroll 1
        for (int j = 0; j < 20; j++) {
          const int s = j & 7;
          if (j < 8) mbar_wait(empty0 + 8 * ((s + 7) & 7), s != 0);
          else mbar_wait(emptyo0 + 8 * s, ((j >> 3) & 1) ^ 1);
          mbar_expect_tx(fullo0 + 8 * s, SLOT_BYTES);
          tma2d(oslot_addr(sbase, s), &P.wo[p], chunk_of(index_at(j >> 1, r, fin), off) * 64, (h0 + (j & 1)) * 192, fullo0 + 8 * s);
        }
        TSTAMP(1); CSTAMP(30);
      }
    } else {
      const int w = warp - 13;
      {
        const uint32_t t0 = clk32();
        uint32_t acc = 0, d0 = 0, d1 = 0, d2 = 0;
        uint32_t due = PF_T0;
        const int l = w * 32 + lane;
        auto pace = [&](int st) {
          bool stop = false;
          while (clk32() - t0 < due) __nanosleep(64);
          if (st >= 24) stop = mbar_test(rdone0, 0);
          due += st < PF_N1 ? PF_DT1 : PF_DT2;
          return stop;
        };
#pragma unroll 1
        for (int st = 0; st < PF_STEPS; st += 3) {
          if (pace(st)) break;
          acc |= d0; d0 = touch_l2(pf_addr(P, st, l, p, tg, hp, off));
          if (pace(st + 1)) break;
          acc |= d1; d1 = touch_l2(pf_addr(P, st + 1, l, p, tg, hp, off));
          if (pace(st + 2)) break;
          acc |= d2; d2 = touch_l2(pf_addr(P, st + 2, l, p, tg, hp, off));
        }
        acc |= d0 | d1 | d2;
        if (out == nullptr) g_flag[0] = acc;
      }
      if (w == 0 && lane == 0) {
#pragma unroll 1
        for (int k = 0; k < 3; k++) {
          const int c = chunk_of(2 * k + r, off), pos = pos_of(2 * k + r, c);
          if (pos >= 4) break;
          mbar_wait(rdone0 + 8 * k, 0);
          HSTAMP(0);
          asm volatile("st.release.gpu.global.u32 [%0], 1;" ::"l"(&g_flag[(grp * 10 + c) * 4 + pos]) : "memory");
          HSTAMP2(0);
        }
      }
      if (w != 0 && lane == 0 && fin) {
        const int c = chunk_of(8 + r, off);
        mbar_wait(rdone0 + 16, 0);
#pragma unroll 1
        for (int g = w - 1; g < 4; g += 2) {
          const int s = 4 + g;
          const int e = (grp * 10 + c) * 4 + g;
          const uint32_t t0 = clk32();
          while (ld_acquire(&g_flag[e]) == 0u) {
            if (clk32() - t0 > SPIN_LIMIT) { DBGREC(1000, g); break; }
          }
          GSTAMP(1, g);
          g_flag[e] = 0u;
          asm volatile("fence.proxy.async.global;" ::: "memory");
          mbar_wait(emptyo0 + 8 * s, 1);
          GSTAMP(2, g);
          mbar_expect_tx(fullo0 + 8 * s, SLOT_BYTES);
          asm volatile("cp.async.bulk.shared::cluster.global.mbarrier::complete_tx::bytes [%0], [%1], %2, [%3];"
                       ::"r"(oslot_addr(sbase, s)), "l"(g_part + (size_t)e * (SLOT_BYTES / 16)), "r"(SLOT_BYTES), "r"(fullo0 + 8 * s) : "memory");
        }
      }
    }
    __syncwarp();
    TDUMP();
  } else {
    asm volatile("setmaxnreg.inc.sync.aligned.u32 160;");
    const int w = warp >> 2;
    const int hf = warp / 3 - w;
    const uint32_t rel0 = mapa(empty0, lane & 1);
    Ring rg{0, 0};
    TSTAMP(0);
    uint32_t o0[48], o1[48];
    const uint32_t never = (out == nullptr);
    do_head(o0, rg, sbase, full0, rel0, w, lane, hf, 1, never);
    do_head(o1, rg, sbase, full0, rel0, w, lane, hf, 4, never);
#pragma unroll
    for (int i = 0; i < 12; i++) o0[i] ^= never;
    fence_regs(o0); fence_regs(o1);

    const int wt = tid & 127;
    const int wnext = w == 2 ? 0 : w + 1;
    if (w == 2) asm volatile("bar.arrive 1, 256;" ::: "memory");
    const uint32_t xb = sbase + XBUF_OFF + w * XBUF_BYTES + wt * 16;
    float a[32];
#pragma unroll 1
    for (int t = 0; t < 10; t++) {
      oproj_chunk(a, o0, o1, t, sbase, fullo0, emptyo0, lane, w, wnext, t < 9 || w < 2);
      const int k = t >> 1;
      TSTAMP(10 + t);
      if (t == 9 && fin) break;
      const int ci = index_at(t, r, fin);
      if ((ci & 1) != r) {
        if (k == 0) mbar_wait(empty0 + 8 * 8, 0);
        else mbar_wait(xempty0 + 8 * w, (k - 1) & 1);
        const uint32_t rxb = mapa(xb, r ^ 1);
        const uint32_t rbar = mapa(xfull0 + 8 * w, r ^ 1);
#pragma unroll
        for (int j = 0; j < 4; j++)
          asm volatile("st.async.weak.shared::cluster.mbarrier::complete_tx::bytes.v4.b32 [%0], {%1, %2, %3, %4}, [%5];"
                       ::"r"(rxb + j * 2048), "r"(pack_bf16(a[8 * j], a[8 * j + 1])), "r"(pack_bf16(a[8 * j + 2], a[8 * j + 3])),
                         "r"(pack_bf16(a[8 * j + 4], a[8 * j + 5])), "r"(pack_bf16(a[8 * j + 6], a[8 * j + 7])), "r"(rbar) : "memory");
      } else {
        mbar_wait(xfull0 + 8 * w, k & 1);
        {
          uint32_t x[16];
          load_tile(x, xb);
          add_tile(a, x);
        }
        if (k < 4) {
          if (wt == 0) mbar_expect_tx(xfull0 + 8 * w, XBUF_BYTES);
          fence_regs(a);
          __syncwarp();
          if (lane == 0) mbar_arrive_cluster(mapa(xempty0 + 8 * w, r ^ 1));
        }
        const int c = chunk_of(ci, off), pos = pos_of(ci, c);
        uint4* dst = (pos < 4 ? g_part + (size_t)((grp * 10 + c) * 4 + pos) * (SLOT_BYTES / 16)
                              : g_late + (size_t)((grp * 10 + c) * 3 + pos - 4) * (SLOT_BYTES / 16)) + w * 512 + wt;
        const uint32_t inv = pos < 4 ? 0u : 0xffffffffu;
#pragma unroll
        for (int j = 0; j < 4; j++)
          asm volatile("st.relaxed.gpu.global.v4.b32 [%0], {%1, %2, %3, %4};"
                       ::"l"(dst + j * 128), "r"(inv ^ pack_bf16(a[8 * j], a[8 * j + 1])), "r"(inv ^ pack_bf16(a[8 * j + 2], a[8 * j + 3])),
                         "r"(inv ^ pack_bf16(a[8 * j + 4], a[8 * j + 5])), "r"(inv ^ pack_bf16(a[8 * j + 6], a[8 * j + 7])) : "memory");
        if (k < 3) {
          __syncwarp();
          if (lane == 0) mbar_arrive(rdone0 + 8 * k);
        }
      }
      TSTAMP(20 + t);
    }
    if (fin) {
      const int c = chunk_of(8 + r, off);
      TSTAMP(7);
      uint4* late = g_late + (size_t)(grp * 10 + c) * 3 * (SLOT_BYTES / 16) + w * 512 + wt;
      uint32_t y[48];
      auto load_late = [&](int q) {
#pragma unroll
        for (int j = 0; j < 4; j++)
          asm volatile("ld.relaxed.gpu.global.v4.b32 {%0, %1, %2, %3}, [%4];"
                       : "=r"(y[16 * q + 4 * j]), "=r"(y[16 * q + 4 * j + 1]), "=r"(y[16 * q + 4 * j + 2]), "=r"(y[16 * q + 4 * j + 3])
                       : "l"(late + q * (SLOT_BYTES / 16) + j * 128) : "memory");
      };
      load_late(0); load_late(1); load_late(2);
      const uint32_t toff = w * XBUF_BYTES + wt * 16;
      {
        uint32_t x0[16], x1[16], x2[16];
        mbar_wait(fullo0 + 8 * 4, 0); load_tile(x0, oslot_addr(sbase, 4) + toff);
        mbar_wait(fullo0 + 8 * 5, 0); load_tile(x1, oslot_addr(sbase, 5) + toff);
        mbar_wait(fullo0 + 8 * 6, 0); load_tile(x2, oslot_addr(sbase, 6) + toff);
        add_tile(a, x0);
        mbar_wait(fullo0 + 8 * 7, 0); load_tile(x0, oslot_addr(sbase, 7) + toff);
        add_tile(a, x1); add_tile(a, x2);
        fence_regs(a);
        TSTAMP(30);
        mbar_wait(xfull0 + 8 * w, 0); load_tile(x1, xb);
        add_tile(a, x0);
        add_tile(a, x1);
      }
      fence_regs(a);
      TSTAMP(31);
      const uint32_t t0 = clk32();
#pragma unroll
      for (int q = 0; q < 3; q++) {
        while (true) {
          bool ok = true;
#pragma unroll
          for (int j = 0; j < 16; j++) ok = ok && (y[16 * q + j] != 0u);
          if (ok || clk32() - t0 > SPIN_LIMIT) break;
          load_late(q);
        }
#pragma unroll
        for (int j = 0; j < 16; j++) {
          a[2 * j] += __uint_as_float(~y[16 * q + j] << 16);
          a[2 * j + 1] += __uint_as_float(~y[16 * q + j] & 0xffff0000u);
        }
      }
      TSTAMP(8);
      const int row = tg * 192 + w * 64 + (wt >> 5) * 16 + ((wt >> 2) & 7);
      uint32_t* d0 = reinterpret_cast<uint32_t*>(out + (size_t)row * 1280 + p * 640 + c * 64 + (wt & 3) * 2);
#pragma unroll
      for (int j = 0; j < 8; j++) {
        d0[j * 4] = pack_bf16(a[4 * j], a[4 * j + 1]);
        d0[j * 4 + 8 * 640] = pack_bf16(a[4 * j + 2], a[4 * j + 3]);
      }
#pragma unroll
      for (int j = 0; j < 12; j++) __stcg(late + (j >> 2) * (SLOT_BYTES / 16) + (j & 3) * 128, make_uint4(0u, 0u, 0u, 0u));
    }
    TSTAMP(9);
    __syncwarp();
    TDUMP();
  }
}

typedef CUresult (*EncodeFn)(CUtensorMap*, CUtensorMapDataType, cuuint32_t, void*, const cuuint64_t*, const cuuint64_t*,
                             const cuuint32_t*, const cuuint32_t*, CUtensorMapInterleave, CUtensorMapSwizzle,
                             CUtensorMapL2promotion, CUtensorMapFloatOOBfill);

static void encode(EncodeFn fn, CUtensorMap* m, const void* ptr, int rank, const cuuint64_t* dims, const cuuint64_t* strides,
                   const cuuint32_t* box) {
  cuuint32_t es[5] = {1, 1, 1, 1, 1};
  fn(m, CU_TENSOR_MAP_DATA_TYPE_BFLOAT16, (cuuint32_t)rank, const_cast<void*>(ptr), dims, strides, box, es,
     CU_TENSOR_MAP_INTERLEAVE_NONE, CU_TENSOR_MAP_SWIZZLE_128B, CU_TENSOR_MAP_L2_PROMOTION_L2_256B,
     CU_TENSOR_MAP_FLOAT_OOB_FILL_NONE);
}

}

extern "C" void kernel_launch(void* const* d_in, const int* in_sizes, int n_in, void* d_out, int out_size) {
  using namespace fk;
  static Params params;
  static const void* cached[10] = {nullptr};
  static EncodeFn fn = nullptr;
  if (!fn) {
    void* f = nullptr;
    cudaDriverEntryPointQueryResult st;
    cudaGetDriverEntryPoint("cuTensorMapEncodeTiled", &f, cudaEnableDefault, &st);
    fn = (EncodeFn)f;
    cudaFuncSetAttribute(fused_kernel, cudaFuncAttributeMaxDynamicSharedMemorySize, SMEM_BYTES);
  }
  bool same = true;
  for (int i = 0; i < 10; i++) same = same && (cached[i] == d_in[i]);
  if (!same) {
    for (int p = 0; p < 2; p++) {
      const void* x = d_in[5 * p + 0];
      const void* k = d_in[5 * p + 1];
      const void* v = d_in[5 * p + 2];
      const void* wq = d_in[5 * p + 3];
      const void* wo = d_in[5 * p + 4];
      params.kp[p] = (const char*)k; params.vp[p] = (const char*)v;
      params.wqp[p] = (const char*)wq; params.wop[p] = (const char*)wo;
      {
        cuuint64_t d[2] = {640, 768}, s[1] = {1280};
        cuuint32_t b[2] = {64, 96};
        encode(fn, &params.x[p], x, 2, d, s, b);
      }
      {
        cuuint64_t d[3] = {64, 640, 96}, s[2] = {12288, 128};
        cuuint32_t b[3] = {64, 64, 3};
        encode(fn, &params.wq[p], wq, 3, d, s, b);
      }
      {
        cuuint64_t d[4] = {192, 48, 32, 16}, s[3] = {384, 18432, 589824};
        cuuint32_t b[4] = {64, 48, 1, 4};
        encode(fn, &params.k[p], k, 4, d, s, b);
        encode(fn, &params.v[p], v, 4, d, s, b);
      }
      {
        cuuint64_t d[2] = {640, 6144}, s[1] = {1280};
        cuuint32_t b[2] = {64, 192};
        encode(fn, &params.wo[p], wo, 2, d, s, b);
      }
    }
    for (int i = 0; i < 10; i++) cached[i] = d_in[i];
  }
  fused_kernel<<<128, NTHREADS, SMEM_BYTES>>>(params, (__nv_bfloat16*)d_out);
}
```

```cpp
#include <cuda_runtime.h>
#include <cuda_bf16.h>
#include <cuda.h>
#include <stdint.h>

#define PF_ON 1
#define PF_T0 1500
#define PF_DT1 1400
#define PF_N1 4
#define PF_DT2 1000
#define CLEAR_AT 0
#define CLEAR_NS 64
#define STOKEN 1
#define STOKEN_AT 9
#define TOKEN 1
#define TOKEN_AT 8
#define FENCE_MODE 1
#define SPIN_LIMIT (1u << 27)

namespace fk {

constexpr int SLOT_BYTES = 24576;
constexpr int NSLOT = 9;
constexpr int NSLOT_O = 8;
constexpr int XBUF_BYTES = 8192;
constexpr int XBUF_OFF = NSLOT_O * SLOT_BYTES;
constexpr int BAR_OFF = NSLOT * SLOT_BYTES;
constexpr int SMEM_BYTES = BAR_OFF + 1024 + 1024;
constexpr int NTHREADS = 512;

struct Params {
  CUtensorMap x[2], wq[2], k[2], v[2], wo[2];
  const char* kp[2]; const char* vp[2]; const char* wqp[2]; const char* wop[2];
};

__device__ uint4 g_part[8 * 10 * 4 * (SLOT_BYTES / 16)];
__device__ unsigned int g_flag[8 * 10 * 4];
__device__ uint4 g_late[2 * 8 * 10 * 3 * (SLOT_BYTES / 16)];
__device__ unsigned int g_epoch[8];
constexpr int LATE_BUF = 8 * 10 * 3 * (SLOT_BYTES / 16);
#define TSTAMP(i)
#define HSTAMP(i)
#define GSTAMP(a, b)
#define HSTAMP2(i)
#define CSTAMP(i)
#define TDUMP()

#define XSTAMP(i)
#define ESTAMP(i) TSTAMP(i)
#define QSTAMP(i)
__device__ __forceinline__ uint32_t smem_u32(const void* p) { return (uint32_t)__cvta_generic_to_shared(p); }
__device__ __forceinline__ void mbar_init(uint32_t bar, uint32_t cnt) {
  asm volatile("mbarrier.init.shared::cta.b64 [%0], %1;" ::"r"(bar), "r"(cnt) : "memory");
}
__device__ __forceinline__ void mbar_expect_tx(uint32_t bar, uint32_t bytes) {
  asm volatile("mbarrier.arrive.expect_tx.shared::cta.b64 _, [%0], %1;" ::"r"(bar), "r"(bytes) : "memory");
}
__device__ __forceinline__ uint32_t mapa(uint32_t addr, uint32_t cta) {
  uint32_t r;
  asm volatile("mapa.shared::cluster.u32 %0, %1, %2;" : "=r"(r) : "r"(addr), "r"(cta));
  return r;
}
__device__ __forceinline__ void mbar_arrive_cluster(uint32_t remote_bar) {
  asm volatile("mbarrier.arrive.shared::cluster.b64 _, [%0];" ::"r"(remote_bar) : "memory");
}
__device__ __forceinline__ uint32_t mbar_try(uint32_t bar, uint32_t parity) {
  uint32_t ok;
  asm volatile("{\n.reg .pred p;\nmbarrier.try_wait.parity.shared::cta.b64 p, [%1], %2;\nselp.u32 %0, 1, 0, p;\n}\n"
               : "=r"(ok) : "r"(bar), "r"(parity) : "memory");
  return ok;
}
__device__ __forceinline__ uint32_t mbar_test(uint32_t bar, uint32_t parity) {
  uint32_t ok;
  asm volatile("{\n.reg .pred p;\nmbarrier.test_wait.parity.shared::cta.b64 p, [%1], %2;\nselp.u32 %0, 1, 0, p;\n}\n"
               : "=r"(ok) : "r"(bar), "r"(parity) : "memory");
  return ok;
}
__device__ __forceinline__ uint32_t mbar_try_cluster(uint32_t bar, uint32_t parity) {
  uint32_t ok;
  asm volatile("{\n.reg .pred p;\nmbarrier.try_wait.parity.acquire.cluster.shared::cta.b64 p, [%1], %2;\nselp.u32 %0, 1, 0, p;\n}\n"
               : "=r"(ok) : "r"(bar), "r"(parity) : "memory");
  return ok;
}
__device__ __forceinline__ uint32_t clk32() {
  uint32_t t;
  asm volatile("mov.u32 %0, %%clock;" : "=r"(t));
  return t;
}
#define DBGREC(a, b)
__device__ __forceinline__ void mbar_wait(uint32_t bar, uint32_t parity) {
  if (mbar_try(bar, parity)) return;
  const uint32_t t0 = clk32();
  while (!mbar_try(bar, parity)) {
    if (clk32() - t0 > SPIN_LIMIT) { DBGREC(bar, parity); break; }
  }
}
__device__ __forceinline__ void mbar_wait_cluster(uint32_t bar, uint32_t parity) {
  if (mbar_try_cluster(bar, parity)) return;
  const uint32_t t0 = clk32();
  while (!mbar_try_cluster(bar, parity)) {
    if (clk32() - t0 > SPIN_LIMIT) break;
  }
}
__device__ __forceinline__ void cluster_sync() {
  asm volatile("barrier.cluster.arrive.release.aligned;\nbarrier.cluster.wait.acquire.aligned;\n" ::: "memory");
}
__device__ __forceinline__ void tma2d(uint32_t dst, const CUtensorMap* m, int c0, int c1, uint32_t bar) {
  asm volatile("cp.async.bulk.tensor.2d.shared::cluster.global.mbarrier::complete_tx::bytes [%0], [%1, {%3, %4}], [%2];"
               ::"r"(dst), "l"(m), "r"(bar), "r"(c0), "r"(c1) : "memory");
}
__device__ __forceinline__ void tma2d_mc(uint32_t dst, const CUtensorMap* m, int c0, int c1, uint32_t bar, uint16_t mask) {
  asm volatile("cp.async.bulk.tensor.2d.shared::cluster.global.mbarrier::complete_tx::bytes.multicast::cluster [%0], [%1, {%3, %4}], [%2], %5;"
               ::"r"(dst), "l"(m), "r"(bar), "r"(c0), "r"(c1), "h"(mask) : "memory");
}
__device__ __forceinline__ void tma3d(uint32_t dst, const CUtensorMap* m, int c0, int c1, int c2, uint32_t bar) {
  asm volatile("cp.async.bulk.tensor.3d.shared::cluster.global.mbarrier::complete_tx::bytes [%0], [%1, {%3, %4, %5}], [%2];"
               ::"r"(dst), "l"(m), "r"(bar), "r"(c0), "r"(c1), "r"(c2) : "memory");
}
__device__ __forceinline__ void tma4d(uint32_t dst, const CUtensorMap* m, int c0, int c1, int c2, int c3, uint32_t bar) {
  asm volatile("cp.async.bulk.tensor.4d.shared::cluster.global.mbarrier::complete_tx::bytes [%0], [%1, {%3, %4, %5, %6}], [%2];"
               ::"r"(dst), "l"(m), "r"(bar), "r"(c0), "r"(c1), "r"(c2), "r"(c3) : "memory");
}
__device__ __forceinline__ void mbar_arrive(uint32_t bar) {
  asm volatile("mbarrier.arrive.shared::cta.b64 _, [%0];" ::"r"(bar) : "memory");
}
__device__ __forceinline__ uint32_t touch_l2(const void* p) {
  uint32_t v;
  asm volatile("ld.global.cg.L2::128B.b32 %0, [%1];" : "=r"(v) : "l"(p));
  return v;
}
__device__ __forceinline__ unsigned ld_acquire(const unsigned* p) {
  unsigned v;
  asm volatile("ld.acquire.gpu.global.u32 %0, [%1];" : "=r"(v) : "l"(p) : "memory");
  return v;
}
__device__ __forceinline__ void wg_fence() { asm volatile("wgmma.fence.sync.aligned;" ::: "memory"); }
__device__ __forceinline__ void wg_commit() { asm volatile("wgmma.commit_group.sync.aligned;" ::: "memory"); }
template <int N> __device__ __forceinline__ void wg_wait() { asm volatile("wgmma.wait_group.sync.aligned %0;" ::"n"(N) : "memory"); }
template <int N> __device__ __forceinline__ void fence_regs(float (&d)[N]) {
#pragma unroll
  for (int i = 0; i < N; i++) asm volatile("" : "+f"(d[i])::"memory");
}
template <int N> __device__ __forceinline__ void fence_regs(uint32_t (&d)[N]) {
#pragma unroll
  for (int i = 0; i < N; i++) asm volatile("" : "+r"(d[i])::"memory");
}
template <int N> __device__ __forceinline__ void pin_regs(const uint32_t* d, uint32_t never, uint32_t addr) {
#pragma unroll
  for (int i = 0; i < N; i += 4)
    asm volatile("{\n.reg .pred p;\nsetp.ne.u32 p, %5, 0;\n@p st.shared.v4.b32 [%0], {%1, %2, %3, %4};\n}\n"
                 ::"r"(addr), "r"(d[i]), "r"(d[i + 1]), "r"(d[i + 2]), "r"(d[i + 3]), "r"(never) : "memory");
}
__device__ __forceinline__ uint32_t pack_bf16(float lo, float hi) {
  uint32_t r;
  asm("cvt.rn.bf16x2.f32 %0, %1, %2;" : "=r"(r) : "f"(hi), "f"(lo));
  return r;
}
__device__ __forceinline__ uint64_t make_desc(uint32_t addr, uint32_t lbo, uint32_t sbo) {
  return (uint64_t)((addr & 0x3FFFFu) >> 4) | ((uint64_t)(lbo >> 4) << 16) | ((uint64_t)(sbo >> 4) << 32) | (1ull << 62);
}

__device__ __forceinline__ void wgmma_n192_ss_tb(float (&d)[96], uint64_t da, uint64_t db, int scale_d) {
  asm volatile("{\n.reg .pred p;\nsetp.ne.b32 p, %98, 0;\n"
    "wgmma.mma_async.sync.aligned.m64n192k16.f32.bf16.bf16 "
    "{%0, %1, %2, %3, %4, %5, %6, %7, %8, %9, %10, %11, %12, %13, %14, %15, %16, %17, %18, %19, %20, %21, %22, %23, %24, %25, %26, %27, %28, %29, %30, %31, %32, %33, %34, %35, %36, %37, %38, %39, %40, %41, %42, %43, %44, %45, %46, %47, %48, %49, %50, %51, %52, %53, %54, %55, %56, %57, %58, %59, %60, %61, %62, %63, %64, %65, %66, %67, %68, %69, %70, %71, %72, %73, %74, %75, %76, %77, %78, %79, %80, %81, %82, %83, %84, %85, %86, %87, %88, %89, %90, %91, %92, %93, %94, %95}, "
    "%96, %97, p, 1, 1, 0, 1;\n}\n"
    : "+f"(d[0]), "+f"(d[1]), "+f"(d[2]), "+f"(d[3]), "+f"(d[4]), "+f"(d[5]), "+f"(d[6]), "+f"(d[7]), "+f"(d[8]), "+f"(d[9]), "+f"(d[10]), "+f"(d[11]), "+f"(d[12]), "+f"(d[13]), "+f"(d[14]), "+f"(d[15]), "+f"(d[16]), "+f"(d[17]), "+f"(d[18]), "+f"(d[19]), "+f"(d[20]), "+f"(d[21]), "+f"(d[22]), "+f"(d[23]), "+f"(d[24]), "+f"(d[25]), "+f"(d[26]), "+f"(d[27]), "+f"(d[28]), "+f"(d[29]), "+f"(d[30]), "+f"(d[31]), "+f"(d[32]), "+f"(d[33]), "+f"(d[34]), "+f"(d[35]), "+f"(d[36]), "+f"(d[37]), "+f"(d[38]), "+f"(d[39]), "+f"(d[40]), "+f"(d[41]), "+f"(d[42]), "+f"(d[43]), "+f"(d[44]), "+f"(d[45]), "+f"(d[46]), "+f"(d[47]), "+f"(d[48]), "+f"(d[49]), "+f"(d[50]), "+f"(d[51]), "+f"(d[52]), "+f"(d[53]), "+f"(d[54]), "+f"(d[55]), "+f"(d[56]), "+f"(d[57]), "+f"(d[58]), "+f"(d[59]), "+f"(d[60]), "+f"(d[61]), "+f"(d[62]), "+f"(d[63]), "+f"(d[64]), "+f"(d[65]), "+f"(d[66]), "+f"(d[67]), "+f"(d[68]), "+f"(d[69]), "+f"(d[70]), "+f"(d[71]), "+f"(d[72]), "+f"(d[73]), "+f"(d[74]), "+f"(d[75]), "+f"(d[76]), "+f"(d[77]), "+f"(d[78]), "+f"(d[79]), "+f"(d[80]), "+f"(d[81]), "+f"(d[82]), "+f"(d[83]), "+f"(d[84]), "+f"(d[85]), "+f"(d[86]), "+f"(d[87]), "+f"(d[88]), "+f"(d[89]), "+f"(d[90]), "+f"(d[91]), "+f"(d[92]), "+f"(d[93]), "+f"(d[94]), "+f"(d[95])
    : "l"(da), "l"(db), "r"(scale_d));
}
__device__ __forceinline__ void wgmma_n96_rs(float (&d)[48], uint32_t a0, uint32_t a1, uint32_t a2, uint32_t a3, uint64_t db, int scale_d) {
  asm volatile("{\n.reg .pred p;\nsetp.ne.b32 p, %53, 0;\n"
    "wgmma.mma_async.sync.aligned.m64n96k16.f32.bf16.bf16 "
    "{%0, %1, %2, %3, %4, %5, %6, %7, %8, %9, %10, %11, %12, %13, %14, %15, %16, %17, %18, %19, %20, %21, %22, %23, %24, %25, %26, %27, %28, %29, %30, %31, %32, %33, %34, %35, %36, %37, %38, %39, %40, %41, %42, %43, %44, %45, %46, %47}, "
    "{%48, %49, %50, %51}, %52, p, 1, 1, 0;\n}\n"
    : "+f"(d[0]), "+f"(d[1]), "+f"(d[2]), "+f"(d[3]), "+f"(d[4]), "+f"(d[5]), "+f"(d[6]), "+f"(d[7]), "+f"(d[8]), "+f"(d[9]), "+f"(d[10]), "+f"(d[11]), "+f"(d[12]), "+f"(d[13]), "+f"(d[14]), "+f"(d[15]), "+f"(d[16]), "+f"(d[17]), "+f"(d[18]), "+f"(d[19]), "+f"(d[20]), "+f"(d[21]), "+f"(d[22]), "+f"(d[23]), "+f"(d[24]), "+f"(d[25]), "+f"(d[26]), "+f"(d[27]), "+f"(d[28]), "+f"(d[29]), "+f"(d[30]), "+f"(d[31]), "+f"(d[32]), "+f"(d[33]), "+f"(d[34]), "+f"(d[35]), "+f"(d[36]), "+f"(d[37]), "+f"(d[38]), "+f"(d[39]), "+f"(d[40]), "+f"(d[41]), "+f"(d[42]), "+f"(d[43]), "+f"(d[44]), "+f"(d[45]), "+f"(d[46]), "+f"(d[47])
    : "r"(a0), "r"(a1), "r"(a2), "r"(a3), "l"(db), "r"(scale_d));
}
__device__ __forceinline__ void wgmma_n64_rs_tb(float (&d)[32], uint32_t a0, uint32_t a1, uint32_t a2, uint32_t a3, uint64_t db, int scale_d) {
  asm volatile("{\n.reg .pred p;\nsetp.ne.b32 p, %37, 0;\n"
    "wgmma.mma_async.sync.aligned.m64n64k16.f32.bf16.bf16 "
    "{%0, %1, %2, %3, %4, %5, %6, %7, %8, %9, %10, %11, %12, %13, %14, %15, %16, %17, %18, %19, %20, %21, %22, %23, %24, %25, %26, %27, %28, %29, %30, %31}, "
    "{%32, %33, %34, %35}, %36, p, 1, 1, 1;\n}\n"
    : "+f"(d[0]), "+f"(d[1]), "+f"(d[2]), "+f"(d[3]), "+f"(d[4]), "+f"(d[5]), "+f"(d[6]), "+f"(d[7]), "+f"(d[8]), "+f"(d[9]), "+f"(d[10]), "+f"(d[11]), "+f"(d[12]), "+f"(d[13]), "+f"(d[14]), "+f"(d[15]), "+f"(d[16]), "+f"(d[17]), "+f"(d[18]), "+f"(d[19]), "+f"(d[20]), "+f"(d[21]), "+f"(d[22]), "+f"(d[23]), "+f"(d[24]), "+f"(d[25]), "+f"(d[26]), "+f"(d[27]), "+f"(d[28]), "+f"(d[29]), "+f"(d[30]), "+f"(d[31])
    : "r"(a0), "r"(a1), "r"(a2), "r"(a3), "l"(db), "r"(scale_d));
}

__device__ __forceinline__ int chunk_of(int i, int off) { const int c = i + off; return c >= 10 ? c - 10 : c; }
__device__ __forceinline__ int pos_of(int i, int c) { return i - (i > chunk_of(c, 6)) - (i > chunk_of(c, 1)); }
__device__ __forceinline__ int index_at(int t, int r, bool fin) { return (r == 0 && (t < 8 || fin)) ? (t ^ 1) : t; }

__device__ __forceinline__ void do_item(const Params& P, int i, int p, int tg, int h0, int r, uint32_t dst, uint32_t bar) {
  const int hh = i >= 26;
  const int j = i - 26 * hh;
  const int h = h0 + hh;
  if (j < 20) {
    const int kc = j >> 1;
    if (!(j & 1)) tma2d_mc(dst + r * 12288, &P.x[p], kc * 64, tg * 192 + r * 96, bar, (uint16_t)3);
    else tma3d(dst, &P.wq[p], 0, kc * 64, h * 3, bar);
  } else if (j < 23) {
    tma4d(dst, &P.k[p], (j - 20) * 64, 0, h, tg * 4, bar);
  } else {
    tma4d(dst, &P.v[p], (j - 23) * 64, 0, h, tg * 4, bar);
  }
}

__device__ __forceinline__ const char* pf_addr(const Params& P, int st, int l, int p, int tg, int hp, int off) {
  const int h0 = hp * 2;
  if (st < 29) {
    if (st >= 12 && st < 17) {
      const int idx = (st - 12) * 96 + l;
      const int k = (idx / 3) * 4 + tg;
      return P.wqp[p] + (size_t)k * 12288 + (h0 + 1) * 384 + (idx % 3) * 128;
    }
    const int hh = st >= 17;
    const int q = st - 17 * hh;
    const char* base = q < 6 ? P.kp[p] : P.vp[p];
    const int idx = (q < 6 ? q : q - 6) * 96 + l;
    const int bb = idx / 144;
    return base + ((size_t)((tg * 4 + bb) * 32 + h0 + hh) * 144 + (idx - bb * 144)) * 128;
  }
  return P.wop[p] + (size_t)(h0 * 192 + tg * 96 + l) * 1280 + chunk_of(st - 29, off) * 128;
}
constexpr int PF_STEPS = 33;

struct Ring {
  uint32_t slot, phase;
  template <int N> __device__ __forceinline__ void advance() {
    if (++slot == N) { slot = 0; phase ^= 1; }
  }
};

__device__ __forceinline__ void do_head(uint32_t (&o)[48], Ring& rg, uint32_t sbase, uint32_t full0, uint32_t rel0,
                                        int w, int lane, int hf, int tbase, uint32_t never) {
  auto release = [&](uint32_t s) { if (lane < 2) mbar_arrive_cluster(rel0 + 8 * s); };
  uint32_t qf[48];
  {
    float acc[96];
    uint32_t psx, psw;
    {
      const uint32_t sx = rg.slot, px = rg.phase; rg.advance<NSLOT>();
      const uint32_t sw = rg.slot, pw = rg.phase; rg.advance<NSLOT>();
      mbar_wait(full0 + 8 * sx, px);
      mbar_wait(full0 + 8 * sw, pw);
      QSTAMP(20);
      const uint64_t da = make_desc(sbase + sx * SLOT_BYTES + w * 8192, 16, 1024);
      const uint64_t db = make_desc(sbase + sw * SLOT_BYTES, 8192, 1024);
      wg_fence();
#pragma unroll
      for (int s = 0; s < 4; s++) wgmma_n192_ss_tb(acc, da + 2 * s, db + 128 * s, s != 0);
      wg_commit();
      psx = sx; psw = sw;
    }
#pragma unroll 1
    for (int kc = 1; kc < 10; kc++) {
      const uint32_t sx = rg.slot, px = rg.phase; rg.advance<NSLOT>();
      const uint32_t sw = rg.slot, pw = rg.phase; rg.advance<NSLOT>();
      mbar_wait(full0 + 8 * sx, px);
      mbar_wait(full0 + 8 * sw, pw);
      QSTAMP(20 + kc);
      const uint64_t da = make_desc(sbase + sx * SLOT_BYTES + w * 8192, 16, 1024);
      const uint64_t db = make_desc(sbase + sw * SLOT_BYTES, 8192, 1024);
      wg_fence();
#pragma unroll
      for (int s = 0; s < 4; s++) wgmma_n192_ss_tb(acc, da + 2 * s, db + 128 * s, 1);
      wg_commit();
      wg_wait<1>(); release(psx); release(psw);
      psx = sx; psw = sw;
    }
    wg_wait<0>();
    fence_regs(acc);
    release(psx); release(psw);
#pragma unroll
    for (int i = 24; i < 48; i++) qf[i] = pack_bf16(acc[2 * i], acc[2 * i + 1]);
    pin_regs<24>(qf + 24, never, full0);
#pragma unroll
    for (int i = 0; i < 24; i++) qf[i] = pack_bf16(acc[2 * i], acc[2 * i + 1]);
    pin_regs<24>(qf, never, full0);
  }
  TSTAMP(tbase + 0);
  uint32_t pa[24];
  {
    float sacc[48];
    uint32_t ks[3];
    fence_regs(qf);
    if (w != 0) asm volatile("bar.sync %0, 256;" ::"r"(1 + w) : "memory");
#pragma unroll
    for (int dc = 0; dc < 3; dc++) {
      ks[dc] = rg.slot;
      mbar_wait(full0 + 8 * rg.slot, rg.phase);
      if (dc == 2) { XSTAMP(19 + tbase); }
      rg.advance<NSLOT>();
      const uint64_t db = make_desc(sbase + ks[dc] * SLOT_BYTES + w * 6144, 16, 1024);
      wg_fence();
#pragma unroll
      for (int s = 0; s < 4; s++) {
        const int j = dc * 4 + s;
        wgmma_n96_rs(sacc, qf[4 * j], qf[4 * j + 1], qf[4 * j + 2], qf[4 * j + 3], db + 2 * s, j != 0);
        if (j == STOKEN_AT && w != 2) asm volatile("bar.arrive %0, 256;" ::"r"(2 + w) : "memory");
      }
    }
    wg_commit();
    wg_wait<0>();
    fence_regs(sacc);
    XSTAMP(20 + tbase);
    release(ks[0]); release(ks[1]); release(ks[2]);
    float v[24];
#pragma unroll
    for (int i = 0; i < 24; i++) v[i] = hf ? sacc[24 + i] : sacc[i];
    float m0 = v[0], m1 = v[2];
#pragma unroll
    for (int t = 0; t < 6; t++) {
      m0 = fmaxf(m0, fmaxf(v[4 * t], v[4 * t + 1]));
      m1 = fmaxf(m1, fmaxf(v[4 * t + 2], v[4 * t + 3]));
    }
    m0 = fmaxf(m0, __shfl_xor_sync(0xffffffffu, m0, 1));
    m1 = fmaxf(m1, __shfl_xor_sync(0xffffffffu, m1, 1));
    m0 = fmaxf(m0, __shfl_xor_sync(0xffffffffu, m0, 2));
    m1 = fmaxf(m1, __shfl_xor_sync(0xffffffffu, m1, 2));
    const float cs = 0.07216878364870322f * 1.4426950408889634f;
    const float b0 = m0 * cs, b1 = m1 * cs;
    float s0 = 0.f, s1 = 0.f;
#pragma unroll
    for (int t = 0; t < 6; t++) {
      v[4 * t] = exp2f(fmaf(v[4 * t], cs, -b0));
      v[4 * t + 1] = exp2f(fmaf(v[4 * t + 1], cs, -b0));
      v[4 * t + 2] = exp2f(fmaf(v[4 * t + 2], cs, -b1));
      v[4 * t + 3] = exp2f(fmaf(v[4 * t + 3], cs, -b1));
      s0 += v[4 * t] + v[4 * t + 1];
      s1 += v[4 * t + 2] + v[4 * t + 3];
    }
    s0 += __shfl_xor_sync(0xffffffffu, s0, 1);
    s1 += __shfl_xor_sync(0xffffffffu, s1, 1);
    s0 += __shfl_xor_sync(0xffffffffu, s0, 2);
    s1 += __shfl_xor_sync(0xffffffffu, s1, 2);
    const float r0 = 1.0f / s0, r1 = 1.0f / s1;
#pragma unroll
    for (int t = 0; t < 6; t++) {
      const uint32_t lo = pack_bf16(v[4 * t] * r0, v[4 * t + 1] * r0);
      const uint32_t hi = pack_bf16(v[4 * t + 2] * r1, v[4 * t + 3] * r1);
      pa[2 * t] = hf ? 0u : lo;
      pa[2 * t + 1] = hf ? 0u : hi;
      pa[12 + 2 * t] = hf ? lo : 0u;
      pa[12 + 2 * t + 1] = hf ? hi : 0u;
    }
  }
  TSTAMP(tbase + 1);
  {
    fence_regs(pa);
    float oa[32], ob[32];
    const uint32_t s0 = rg.slot, p0 = rg.phase; rg.advance<NSLOT>();
    const uint32_t s1 = rg.slot, p1 = rg.phase; rg.advance<NSLOT>();
    const uint32_t s2 = rg.slot, p2 = rg.phase; rg.advance<NSLOT>();
    mbar_wait(full0 + 8 * s0, p0);
    {
      const uint64_t db = make_desc(sbase + s0 * SLOT_BYTES + w * 6144, 16, 1024);
      wg_fence();
#pragma unroll
      for (int j = 0; j < 6; j++) wgmma_n64_rs_tb(oa, pa[4 * j], pa[4 * j + 1], pa[4 * j + 2], pa[4 * j + 3], db + 128 * j, j != 0);
    }
    mbar_wait(full0 + 8 * s1, p1);
    XSTAMP(21 + tbase);
    {
      const uint64_t db = make_desc(sbase + s1 * SLOT_BYTES + w * 6144, 16, 1024);
      wg_fence();
#pragma unroll
      for (int j = 0; j < 6; j++) wgmma_n64_rs_tb(ob, pa[4 * j], pa[4 * j + 1], pa[4 * j + 2], pa[4 * j + 3], db + 128 * j, j != 0);
    }
    wg_commit();
    wg_wait<0>();
    fence_regs(oa); fence_regs(ob);
    release(s0); release(s1);
#pragma unroll
    for (int i = 0; i < 16; i++) o[i] = pack_bf16(oa[2 * i], oa[2 * i + 1]);
    pin_regs<16>(o, never, full0);
#pragma unroll
    for (int i = 0; i < 16; i++) o[16 + i] = pack_bf16(ob[2 * i], ob[2 * i + 1]);
    pin_regs<16>(o + 16, never, full0);
    float oc[32];
    XSTAMP(25 + tbase / 4 * 2);
    mbar_wait(full0 + 8 * s2, p2);
    XSTAMP(26 + tbase / 4 * 2);
    {
      const uint64_t db = make_desc(sbase + s2 * SLOT_BYTES + w * 6144, 16, 1024);
      wg_fence();
#pragma unroll
      for (int j = 0; j < 6; j++) wgmma_n64_rs_tb(oc, pa[4 * j], pa[4 * j + 1], pa[4 * j + 2], pa[4 * j + 3], db + 128 * j, j != 0);
    }
    wg_commit();
    wg_wait<0>();
    fence_regs(oc);
    release(s2);
#pragma unroll
    for (int i = 0; i < 16; i++) o[32 + i] = pack_bf16(oc[2 * i], oc[2 * i + 1]);
    pin_regs<16>(o + 32, never, full0);
  }
  TSTAMP(tbase + 2);
}

__device__ __forceinline__ uint32_t oslot_addr(uint32_t sbase, uint32_t s) { return sbase + ((s + 7) & 7) * SLOT_BYTES; }
__device__ __forceinline__ void oproj_chunk(float (&a)[32], const uint32_t (&o0)[48], const uint32_t (&o1)[48], int t,
                                            uint32_t sbase, uint32_t fullo0, uint32_t emptyo0, int lane, int w, int wnext, bool pass) {
  const uint32_t s0 = (2 * t) & 7, s1 = s0 + 1, ph = (t >> 2) & 1;
  mbar_wait(fullo0 + 8 * s0, ph);
  mbar_wait(fullo0 + 8 * s1, ph);
  asm volatile("bar.sync %0, 256;" ::"r"(1 + w) : "memory");
  {
    const uint64_t db = make_desc(oslot_addr(sbase, s0), 16, 1024);
    wg_fence();
#pragma unroll
    for (int j = 0; j < 12; j++)
      wgmma_n64_rs_tb(a, o0[4 * j], o0[4 * j + 1], o0[4 * j + 2], o0[4 * j + 3], db + 128 * j, j != 0);
    wg_commit();
  }
  {
    const uint64_t db = make_desc(oslot_addr(sbase, s1), 16, 1024);
#pragma unroll
    for (int j = 0; j < 12; j++) {
      wgmma_n64_rs_tb(a, o1[4 * j], o1[4 * j + 1], o1[4 * j + 2], o1[4 * j + 3], db + 128 * j, 1);
      if (j == TOKEN_AT && pass) asm volatile("bar.arrive %0, 256;" ::"r"(1 + wnext) : "memory");
    }
    wg_commit();
  }
  wg_wait<1>();
  if (lane == 0) mbar_arrive(emptyo0 + 8 * s0);
  wg_wait<0>();
  fence_regs(a);
  if (lane == 0) mbar_arrive(emptyo0 + 8 * s1);
}

__device__ __forceinline__ void load_tile(uint32_t (&x)[16], uint32_t addr) {
#pragma unroll
  for (int j = 0; j < 4; j++)
    asm volatile("ld.shared.v4.b32 {%0, %1, %2, %3}, [%4];"
                 : "=r"(x[4 * j]), "=r"(x[4 * j + 1]), "=r"(x[4 * j + 2]), "=r"(x[4 * j + 3]) : "r"(addr + j * 2048) : "memory");
}
__device__ __forceinline__ void add_tile(float (&a)[32], const uint32_t (&x)[16]) {
#pragma unroll
  for (int j = 0; j < 16; j++) {
    a[2 * j] += __uint_as_float(x[j] << 16);
    a[2 * j + 1] += __uint_as_float(x[j] & 0xffff0000u);
  }
}

__global__ void __cluster_dims__(2, 1, 1) __launch_bounds__(NTHREADS, 1)
fused_kernel(const __grid_constant__ Params P, __nv_bfloat16* __restrict__ out) {
  extern __shared__ uint8_t smem_raw[];
  const uint32_t sbase = (smem_u32(smem_raw) + 1023u) & ~1023u;
  const uint32_t full0 = sbase + BAR_OFF;
  const uint32_t empty0 = full0 + 72;
  const uint32_t xfull0 = full0 + 144;
  const uint32_t xempty0 = full0 + 168;
  const uint32_t fullo0 = full0 + 192;
  const uint32_t emptyo0 = full0 + 256;
  const uint32_t rdone0 = full0 + 320;
  const uint32_t eready = full0 + 344;
  const uint32_t epoch_s = full0 + 352;

  const int tid = threadIdx.x, lane = tid & 31;
  const int warp = __shfl_sync(0xffffffffu, tid >> 5, 0);
  const int bid = blockIdx.x;
  const int hp = bid & 15, tg = (bid >> 4) & 3, p = bid >> 6;
  const int r = hp & 1;
  const int h0 = hp * 2;
  const int grp = p * 4 + tg;
  const int off = (hp >> 1) + (hp >> 3);
  const bool fin = r == 1 || off == 0 || off == 5;

  if (tid == 384) {
    asm volatile("prefetch.tensormap [%0];" ::"l"(&P.wq[p]) : "memory");
    asm volatile("prefetch.tensormap [%0];" ::"l"(&P.x[p]) : "memory");
    for (int i = 0; i < NSLOT; i++) { mbar_init(full0 + 8 * i, 1); mbar_init(empty0 + 8 * i, 24); }
    for (int i = 0; i < 3; i++) { mbar_init(xfull0 + 8 * i, 1); mbar_init(xempty0 + 8 * i, 4); }
    for (int i = 0; i < 3; i++) mbar_init(rdone0 + 8 * i, 12);
    mbar_init(eready, 3);
    for (int i = 0; i < NSLOT_O; i++) { mbar_init(fullo0 + 8 * i, 1); mbar_init(emptyo0 + 8 * i, 12); }
    asm volatile("fence.mbarrier_init.release.cluster;" ::: "memory");
    for (int i = 0; i < NSLOT; i++) mbar_expect_tx(full0 + 8 * i, SLOT_BYTES);
    for (int i = 1; i < NSLOT; i += 2) do_item(P, i, p, tg, h0, r, sbase + i * SLOT_BYTES, full0 + 8 * i);
    for (int i = 0; i < 3; i++) mbar_expect_tx(xfull0 + 8 * i, XBUF_BYTES);
    asm volatile("prefetch.tensormap [%0];" ::"l"(&P.k[p]) : "memory");
    asm volatile("prefetch.tensormap [%0];" ::"l"(&P.v[p]) : "memory");
    asm volatile("prefetch.tensormap [%0];" ::"l"(&P.wo[p]) : "memory");
  }
  __syncwarp();
  asm volatile("barrier.cluster.arrive.relaxed.aligned;\nbarrier.cluster.wait.aligned;\n" ::: "memory");

  if (warp >= 12) {
    asm volatile("setmaxnreg.dec.sync.aligned.u32 32;");
    if (warp == 12) {
      if (lane == 0) {
        TSTAMP(0); CSTAMP(28);
#pragma unroll 1
        for (int i = 0; i < NSLOT; i += 2) do_item(P, i, p, tg, h0, r, sbase + i * SLOT_BYTES, full0 + 8 * i);
        uint32_t slot = 0, phase = 1;
#pragma unroll 1
        for (int i = NSLOT; i < 52; i++) {
          mbar_wait(empty0 + 8 * slot, phase ^ 1);
          mbar_expect_tx(full0 + 8 * slot, SLOT_BYTES);
          do_item(P, i, p, tg, h0, r, sbase + slot * SLOT_BYTES, full0 + 8 * slot);
          if (++slot == NSLOT) { slot = 0; phase ^= 1; }
        }
        TSTAMP(2); CSTAMP(29);
#pragma unroll 1
        for (int j = 0; j < 20; j++) {
          const int s = j & 7;
          if (j < 8) mbar_wait(empty0 + 8 * ((s + 7) & 7), s != 0);
          else mbar_wait(emptyo0 + 8 * s, ((j >> 3) & 1) ^ 1);
          mbar_expect_tx(fullo0 + 8 * s, SLOT_BYTES);
          tma2d(oslot_addr(sbase, s), &P.wo[p], chunk_of(index_at(j >> 1, r, fin), off) * 64, (h0 + (j & 1)) * 192, fullo0 + 8 * s);
        }
        TSTAMP(1); CSTAMP(30);
      }
    } else {
      const int w = warp - 13;
      unsigned epoch;
      asm volatile("ld.global.cg.u32 %0, [%1];" : "=r"(epoch) : "l"(&g_epoch[grp]));
      auto post_epoch = [&]() {
        if (lane == 0) {
          asm volatile("st.shared.u32 [%0], %1;" ::"r"(epoch_s), "r"(epoch) : "memory");
          mbar_arrive(eready);
        }
      };
      {
        const uint32_t t0 = clk32();
        uint32_t acc = 0, d0 = 0, d1 = 0, d2 = 0;
        uint32_t due = PF_T0;
        const int l = w * 32 + lane;
        auto pace = [&](int st) {
          bool stop = false;
          while (clk32() - t0 < due) __nanosleep(64);
          if (st >= 24) stop = mbar_test(rdone0, 0);
          due += st < PF_N1 ? PF_DT1 : PF_DT2;
          return stop;
        };
#pragma unroll 1
        for (int st = 0; st < PF_STEPS; st += 3) {
          if (pace(st)) break;
          if (st == 3) post_epoch();
          acc |= d0; d0 = touch_l2(pf_addr(P, st, l, p, tg, hp, off));
          if (pace(st + 1)) break;
          acc |= d1; d1 = touch_l2(pf_addr(P, st + 1, l, p, tg, hp, off));
          if (pace(st + 2)) break;
          acc |= d2; d2 = touch_l2(pf_addr(P, st + 2, l, p, tg, hp, off));
        }
        acc |= d0 | d1 | d2;
        if (out == nullptr) g_flag[0] = acc;
      }
      if (w != 0) {
        mbar_wait(rdone0 + 8 * CLEAR_AT, 0);
#pragma unroll 1
        for (int i = 4 + r; i < 9; i += 2) {
          const int c = chunk_of(i, off), pos = pos_of(i, c);
          if (pos < 4 || pos > 6) continue;
          uint4* dst = g_late + (~epoch & 1u) * LATE_BUF + ((grp * 10 + c) * 3 + pos - 4) * (SLOT_BYTES / 16) + (w - 1) * 768 + lane;
#pragma unroll 1
          for (int j = 0; j < 24; j++) {
            __stcg(dst + j * 32, make_uint4(0u, 0u, 0u, 0u));
            __nanosleep(CLEAR_NS);
          }
        }
      }
      if (w == 0 && lane == 0) {
#pragma unroll 1
        for (int k = 0; k < 3; k++) {
          const int c = chunk_of(2 * k + r, off), pos = pos_of(2 * k + r, c);
          if (pos >= 4) break;
          mbar_wait(rdone0 + 8 * k, 0);
          HSTAMP(0);
          asm volatile("st.release.gpu.global.u32 [%0], 1;" ::"l"(&g_flag[(grp * 10 + c) * 4 + pos]) : "memory");
          HSTAMP2(0);
        }
      }
      if (w != 0 && lane == 0 && fin) {
        const int c = chunk_of(8 + r, off);
        mbar_wait(rdone0 + 16, 0);
#pragma unroll 1
        for (int g = w - 1; g < 4; g += 2) {
          const int s = 4 + g;
          const int e = (grp * 10 + c) * 4 + g;
          const uint32_t t0 = clk32();
          while (ld_acquire(&g_flag[e]) == 0u) {
            if (clk32() - t0 > SPIN_LIMIT) { DBGREC(1000, g); break; }
          }
          GSTAMP(1, g);
          g_flag[e] = 0u;
          asm volatile("fence.proxy.async.global;" ::: "memory");
          mbar_wait(emptyo0 + 8 * s, 1);
          GSTAMP(2, g);
          mbar_expect_tx(fullo0 + 8 * s, SLOT_BYTES);
          asm volatile("cp.async.bulk.shared::cluster.global.mbarrier::complete_tx::bytes [%0], [%1], %2, [%3];"
                       ::"r"(oslot_addr(sbase, s)), "l"(g_part + (size_t)e * (SLOT_BYTES / 16)), "r"(SLOT_BYTES), "r"(fullo0 + 8 * s) : "memory");
        }
      }
    }
    __syncwarp();
    TDUMP();
  } else {
    asm volatile("setmaxnreg.inc.sync.aligned.u32 160;");
    const int w = warp >> 2;
    const int hf = warp / 3 - w;
    const uint32_t rel0 = mapa(empty0, lane & 1);
    Ring rg{0, 0};
    TSTAMP(0);
    uint32_t o0[48], o1[48];
    const uint32_t never = (out == nullptr);
    do_head(o0, rg, sbase, full0, rel0, w, lane, hf, 1, never);
    do_head(o1, rg, sbase, full0, rel0, w, lane, hf, 4, never);
#pragma unroll
    for (int i = 0; i < 12; i++) o0[i] ^= never;
    fence_regs(o0); fence_regs(o1);

    const int wt = tid & 127;
    const int wnext = w == 2 ? 0 : w + 1;
    if (w == 2) asm volatile("bar.arrive 1, 256;" ::: "memory");
    const uint32_t xb = sbase + XBUF_OFF + w * XBUF_BYTES + wt * 16;
    mbar_wait(eready, 0);
    auto late_base = [&]() {
      unsigned e;
      asm volatile("ld.shared.u32 %0, [%1];" : "=r"(e) : "r"(epoch_s) : "memory");
      return g_late + (e & 1u) * LATE_BUF;
    };
    float a[32];
#pragma unroll 1
    for (int t = 0; t < 10; t++) {
      oproj_chunk(a, o0, o1, t, sbase, fullo0, emptyo0, lane, w, wnext, t < 9 || w < 2);
      const int k = t >> 1;
      TSTAMP(10 + t);
      if (t == 9 && fin) break;
      const int ci = index_at(t, r, fin);
      if ((ci & 1) != r) {
        if (k == 0) mbar_wait(empty0 + 8 * 8, 0);
        else mbar_wait(xempty0 + 8 * w, (k - 1) & 1);
        const uint32_t rxb = mapa(xb, r ^ 1);
        const uint32_t rbar = mapa(xfull0 + 8 * w, r ^ 1);
#pragma unroll
        for (int j = 0; j < 4; j++)
          asm volatile("st.async.weak.shared::cluster.mbarrier::complete_tx::bytes.v4.b32 [%0], {%1, %2, %3, %4}, [%5];"
                       ::"r"(rxb + j * 2048), "r"(pack_bf16(a[8 * j], a[8 * j + 1])), "r"(pack_bf16(a[8 * j + 2], a[8 * j + 3])),
                         "r"(pack_bf16(a[8 * j + 4], a[8 * j + 5])), "r"(pack_bf16(a[8 * j + 6], a[8 * j + 7])), "r"(rbar) : "memory");
      } else {
        mbar_wait(xfull0 + 8 * w, k & 1);
        {
          uint32_t x[16];
          load_tile(x, xb);
          add_tile(a, x);
        }
        if (k < 4) {
          if (wt == 0) mbar_expect_tx(xfull0 + 8 * w, XBUF_BYTES);
          fence_regs(a);
          __syncwarp();
          if (lane == 0) mbar_arrive_cluster(mapa(xempty0 + 8 * w, r ^ 1));
        }
        const int c = chunk_of(ci, off), pos = pos_of(ci, c);
        uint4* dst = (pos < 4 ? g_part + (size_t)((grp * 10 + c) * 4 + pos) * (SLOT_BYTES / 16)
                              : late_base() + ((grp * 10 + c) * 3 + pos - 4) * (SLOT_BYTES / 16)) + w * 512 + wt;
        const uint32_t inv = pos < 4 ? 0u : 0xffffffffu;
#pragma unroll
        for (int j = 0; j < 4; j++)
          asm volatile("st.relaxed.gpu.global.v4.b32 [%0], {%1, %2, %3, %4};"
                       ::"l"(dst + j * 128), "r"(inv ^ pack_bf16(a[8 * j], a[8 * j + 1])), "r"(inv ^ pack_bf16(a[8 * j + 2], a[8 * j + 3])),
                         "r"(inv ^ pack_bf16(a[8 * j + 4], a[8 * j + 5])), "r"(inv ^ pack_bf16(a[8 * j + 6], a[8 * j + 7])) : "memory");
        if (k < 3) {
          __syncwarp();
          if (lane == 0) mbar_arrive(rdone0 + 8 * k);
        }
      }
      ESTAMP(20 + t);
    }
    if (fin) {
      const int c = chunk_of(8 + r, off);
      TSTAMP(7);
      const uint4* late = late_base() + (grp * 10 + c) * 3 * (SLOT_BYTES / 16) + w * 512 + wt;
      uint32_t y[48];
      auto load_late = [&](int q) {
#pragma unroll
        for (int j = 0; j < 4; j++)
          asm volatile("ld.relaxed.gpu.global.v4.b32 {%0, %1, %2, %3}, [%4];"
                       : "=r"(y[16 * q + 4 * j]), "=r"(y[16 * q + 4 * j + 1]), "=r"(y[16 * q + 4 * j + 2]), "=r"(y[16 * q + 4 * j + 3])
                       : "l"(late + q * (SLOT_BYTES / 16) + j * 128) : "memory");
      };
      const uint32_t toff = w * XBUF_BYTES + wt * 16;
      {
        uint32_t x0[16], x1[16], x2[16];
        load_late(0); load_late(1); load_late(2);
        mbar_wait(fullo0 + 8 * 4, 0); load_tile(x0, oslot_addr(sbase, 4) + toff);
        mbar_wait(fullo0 + 8 * 5, 0); load_tile(x1, oslot_addr(sbase, 5) + toff);
        mbar_wait(fullo0 + 8 * 6, 0); load_tile(x2, oslot_addr(sbase, 6) + toff);
        add_tile(a, x0);
        mbar_wait(fullo0 + 8 * 7, 0); load_tile(x0, oslot_addr(sbase, 7) + toff);
        add_tile(a, x1); add_tile(a, x2);
        fence_regs(a);
        TSTAMP(30);
        mbar_wait(xfull0 + 8 * w, 0); load_tile(x1, xb);
        add_tile(a, x0);
        add_tile(a, x1);
      }
      fence_regs(a);
      TSTAMP(31);
      const uint32_t t0 = clk32();
#pragma unroll
      for (int q = 0; q < 3; q++) {
        while (true) {
          bool ok = true;
#pragma unroll
          for (int j = 0; j < 16; j++) ok = ok && (y[16 * q + j] != 0u);
          if (ok || clk32() - t0 > SPIN_LIMIT) break;
          load_late(q);
        }
#pragma unroll
        for (int j = 0; j < 16; j++) {
          a[2 * j] += __uint_as_float(~y[16 * q + j] << 16);
          a[2 * j + 1] += __uint_as_float(~y[16 * q + j] & 0xffff0000u);
        }
      }
      TSTAMP(8);
      const int row = tg * 192 + w * 64 + (wt >> 5) * 16 + ((wt >> 2) & 7);
      uint4* d0 = reinterpret_cast<uint4*>(out + (size_t)row * 1280 + p * 640 + c * 64 + (wt & 3) * 8);
      const bool b0 = wt & 1, b1 = wt & 2;
      __syncwarp();
#pragma unroll
      for (int u = 0; u < 4; u++) {
        uint32_t x[4];
#pragma unroll
        for (int i = 0; i < 4; i++) {
          const int j = (u & 1) * 4 + i;
          x[i] = pack_bf16(a[4 * j + (u >> 1) * 2], a[4 * j + (u >> 1) * 2 + 1]);
        }
        uint32_t v;
        v = __shfl_xor_sync(0xffffffffu, b0 ? x[0] : x[1], 1); if (b0) x[0] = v; else x[1] = v;
        v = __shfl_xor_sync(0xffffffffu, b0 ? x[2] : x[3], 1); if (b0) x[2] = v; else x[3] = v;
        v = __shfl_xor_sync(0xffffffffu, b1 ? x[0] : x[2], 2); if (b1) x[0] = v; else x[2] = v;
        v = __shfl_xor_sync(0xffffffffu, b1 ? x[1] : x[3], 2); if (b1) x[1] = v; else x[3] = v;
        d0[(u & 1) * 4 + (u >> 1) * 8 * 160] = make_uint4(x[0], x[1], x[2], x[3]);
      }
      if (hp == 1 && tid == 0) asm volatile("red.relaxed.gpu.global.add.u32 [%0], 1;" ::"l"(&g_epoch[grp]) : "memory");
    }
    TSTAMP(9);
    __syncwarp();
    TDUMP();
  }
}

typedef CUresult (*EncodeFn)(CUtensorMap*, CUtensorMapDataType, cuuint32_t, void*, const cuuint64_t*, const cuuint64_t*,
                             const cuuint32_t*, const cuuint32_t*, CUtensorMapInterleave, CUtensorMapSwizzle,
                             CUtensorMapL2promotion, CUtensorMapFloatOOBfill);

static void encode(EncodeFn fn, CUtensorMap* m, const void* ptr, int rank, const cuuint64_t* dims, const cuuint64_t* strides,
                   const cuuint32_t* box) {
  cuuint32_t es[5] = {1, 1, 1, 1, 1};
  fn(m, CU_TENSOR_MAP_DATA_TYPE_BFLOAT16, (cuuint32_t)rank, const_cast<void*>(ptr), dims, strides, box, es,
     CU_TENSOR_MAP_INTERLEAVE_NONE, CU_TENSOR_MAP_SWIZZLE_128B, CU_TENSOR_MAP_L2_PROMOTION_L2_256B,
     CU_TENSOR_MAP_FLOAT_OOB_FILL_NONE);
}

}

extern "C" void kernel_launch(void* const* d_in, const int* in_sizes, int n_in, void* d_out, int out_size) {
  using namespace fk;
  static Params params;
  static const void* cached[10] = {nullptr};
  static EncodeFn fn = nullptr;
  if (!fn) {
    void* f = nullptr;
    cudaDriverEntryPointQueryResult st;
    cudaGetDriverEntryPoint("cuTensorMapEncodeTiled", &f, cudaEnableDefault, &st);
    fn = (EncodeFn)f;
    cudaFuncSetAttribute(fused_kernel, cudaFuncAttributeMaxDynamicSharedMemorySize, SMEM_BYTES);
  }
  bool same = true;
  for (int i = 0; i < 10; i++) same = same && (cached[i] == d_in[i]);
  if (!same) {
    for (int p = 0; p < 2; p++) {
      const void* x = d_in[5 * p + 0];
      const void* k = d_in[5 * p + 1];
      const void* v = d_in[5 * p + 2];
      const void* wq = d_in[5 * p + 3];
      const void* wo = d_in[5 * p + 4];
      params.kp[p] = (const char*)k; params.vp[p] = (const char*)v;
      params.wqp[p] = (const char*)wq; params.wop[p] = (const char*)wo;
      {
        cuuint64_t d[2] = {640, 768}, s[1] = {1280};
        cuuint32_t b[2] = {64, 96};
        encode(fn, &params.x[p], x, 2, d, s, b);
      }
      {
        cuuint64_t d[3] = {64, 640, 96}, s[2] = {12288, 128};
        cuuint32_t b[3] = {64, 64, 3};
        encode(fn, &params.wq[p], wq, 3, d, s, b);
      }
      {
        cuuint64_t d[4] = {192, 48, 32, 16}, s[3] = {384, 18432, 589824};
        cuuint32_t b[4] = {64, 48, 1, 4};
        encode(fn, &params.k[p], k, 4, d, s, b);
        encode(fn, &params.v[p], v, 4, d, s, b);
      }
      {
        cuuint64_t d[2] = {640, 6144}, s[1] = {1280};
        cuuint32_t b[2] = {64, 192};
        encode(fn, &params.wo[p], wo, 2, d, s, b);
      }
    }
    for (int i = 0; i < 10; i++) cached[i] = d_in[i];
  }
  fused_kernel<<<128, NTHREADS, SMEM_BYTES>>>(params, (__nv_bfloat16*)d_out);
}
```

```cpp
#include <cuda_runtime.h>
#include <cuda_bf16.h>
#include <cuda.h>
#include <stdint.h>

#define PF_ON 1
#define PF_WIN 4
#define PF_WIN1 3
#define PF_NW 2
#define QMMA 4
#define TOKEN_AT 8
#define SPIN_LIMIT (1u << 27)

namespace fk {

#define HEADMAP 0
constexpr int HM = HEADMAP ? 1 : 2, HS = HEADMAP ? 16 : 1;
constexpr int SLOT_BYTES = 24576;
constexpr int NSLOT = 9;
constexpr int NSLOT_O = 8;
constexpr int XBUF_BYTES = 8192;
constexpr int XBUF_OFF = NSLOT_O * SLOT_BYTES;
constexpr int BAR_OFF = NSLOT * SLOT_BYTES;
constexpr int FULLO = 192, EMPTYE = 360;
constexpr int SINK_OFF = BAR_OFF + 1024;
constexpr int SMEM_BYTES = SINK_OFF + PF_WIN * 768 + 1024;
constexpr int NTHREADS = 512;

struct Params {
  CUtensorMap x[2], wq[2], k[2], v[2], wo[2];
  const char* kp[2]; const char* vp[2]; const char* wqp[2]; const char* wop[2];
};

__device__ uint4 g_part[8 * 10 * 7 * (SLOT_BYTES / 16)];
__device__ unsigned int g_epoch[8];
#define TSTAMP(i)
#define PSTAMP(i)
#define HSTAMP(i)
#define GSTAMP(a, b)
#define HSTAMP2(i)
#define CSTAMP(i)
#define TDUMP()

#define XSTAMP(i)
#define ESTAMP(i) TSTAMP(i)
#define QSTAMP(i)
#define FSTAMP(i)
__device__ __forceinline__ uint32_t smem_u32(const void* p) { return (uint32_t)__cvta_generic_to_shared(p); }
__device__ __forceinline__ void mbar_init(uint32_t bar, uint32_t cnt) {
  asm volatile("mbarrier.init.shared::cta.b64 [%0], %1;" ::"r"(bar), "r"(cnt) : "memory");
}
__device__ __forceinline__ void mbar_expect_tx(uint32_t bar, uint32_t bytes) {
  asm volatile("mbarrier.arrive.expect_tx.shared::cta.b64 _, [%0], %1;" ::"r"(bar), "r"(bytes) : "memory");
}
__device__ __forceinline__ uint32_t mapa(uint32_t addr, uint32_t cta) {
  uint32_t r;
  asm volatile("mapa.shared::cluster.u32 %0, %1, %2;" : "=r"(r) : "r"(addr), "r"(cta));
  return r;
}
__device__ __forceinline__ void mbar_arrive_cluster(uint32_t remote_bar) {
  asm volatile("mbarrier.arrive.shared::cluster.b64 _, [%0];" ::"r"(remote_bar) : "memory");
}
__device__ __forceinline__ uint32_t mbar_try(uint32_t bar, uint32_t parity) {
  uint32_t ok;
  asm volatile("{\n.reg .pred p;\nmbarrier.try_wait.parity.shared::cta.b64 p, [%1], %2;\nselp.u32 %0, 1, 0, p;\n}\n"
               : "=r"(ok) : "r"(bar), "r"(parity) : "memory");
  return ok;
}
__device__ __forceinline__ uint32_t mbar_test(uint32_t bar, uint32_t parity) {
  uint32_t ok;
  asm volatile("{\n.reg .pred p;\nmbarrier.test_wait.parity.shared::cta.b64 p, [%1], %2;\nselp.u32 %0, 1, 0, p;\n}\n"
               : "=r"(ok) : "r"(bar), "r"(parity) : "memory");
  return ok;
}
__device__ __forceinline__ uint32_t mbar_try_cluster(uint32_t bar, uint32_t parity) {
  uint32_t ok;
  asm volatile("{\n.reg .pred p;\nmbarrier.try_wait.parity.acquire.cluster.shared::cta.b64 p, [%1], %2;\nselp.u32 %0, 1, 0, p;\n}\n"
               : "=r"(ok) : "r"(bar), "r"(parity) : "memory");
  return ok;
}
__device__ __forceinline__ uint32_t clk32() {
  uint32_t t;
  asm volatile("mov.u32 %0, %%clock;" : "=r"(t));
  return t;
}
#define DBGREC(a, b)
__device__ __forceinline__ void mbar_wait(uint32_t bar, uint32_t parity) {
  if (mbar_try(bar, parity)) return;
  const uint32_t t0 = clk32();
  while (!mbar_try(bar, parity)) {
    if (clk32() - t0 > SPIN_LIMIT) { DBGREC(bar, parity); break; }
  }
}
__device__ __forceinline__ void mbar_wait_cluster(uint32_t bar, uint32_t parity) {
  if (mbar_try_cluster(bar, parity)) return;
  const uint32_t t0 = clk32();
  while (!mbar_try_cluster(bar, parity)) {
    if (clk32() - t0 > SPIN_LIMIT) break;
  }
}
__device__ __forceinline__ void cluster_sync() {
  asm volatile("barrier.cluster.arrive.release.aligned;\nbarrier.cluster.wait.acquire.aligned;\n" ::: "memory");
}
__device__ __forceinline__ void tma2d(uint32_t dst, const CUtensorMap* m, int c0, int c1, uint32_t bar) {
  asm volatile("cp.async.bulk.tensor.2d.shared::cluster.global.mbarrier::complete_tx::bytes [%0], [%1, {%3, %4}], [%2];"
               ::"r"(dst), "l"(m), "r"(bar), "r"(c0), "r"(c1) : "memory");
}
__device__ __forceinline__ void tma2d_mc(uint32_t dst, const CUtensorMap* m, int c0, int c1, uint32_t bar, uint16_t mask) {
  asm volatile("cp.async.bulk.tensor.2d.shared::cluster.global.mbarrier::complete_tx::bytes.multicast::cluster [%0], [%1, {%3, %4}], [%2], %5;"
               ::"r"(dst), "l"(m), "r"(bar), "r"(c0), "r"(c1), "h"(mask) : "memory");
}
__device__ __forceinline__ void tma3d(uint32_t dst, const CUtensorMap* m, int c0, int c1, int c2, uint32_t bar) {
  asm volatile("cp.async.bulk.tensor.3d.shared::cluster.global.mbarrier::complete_tx::bytes [%0], [%1, {%3, %4, %5}], [%2];"
               ::"r"(dst), "l"(m), "r"(bar), "r"(c0), "r"(c1), "r"(c2) : "memory");
}
__device__ __forceinline__ void tma4d(uint32_t dst, const CUtensorMap* m, int c0, int c1, int c2, int c3, uint32_t bar) {
  asm volatile("cp.async.bulk.tensor.4d.shared::cluster.global.mbarrier::complete_tx::bytes [%0], [%1, {%3, %4, %5, %6}], [%2];"
               ::"r"(dst), "l"(m), "r"(bar), "r"(c0), "r"(c1), "r"(c2), "r"(c3) : "memory");
}
__device__ __forceinline__ void mbar_arrive(uint32_t bar) {
  asm volatile("mbarrier.arrive.shared::cta.b64 _, [%0];" ::"r"(bar) : "memory");
}
__device__ __forceinline__ uint32_t touch_l2(const void* p) {
  uint32_t v;
  asm volatile("ld.global.cg.L2::128B.b32 %0, [%1];" : "=r"(v) : "l"(p));
  return v;
}
__device__ __forceinline__ unsigned ld_acquire(const unsigned* p) {
  unsigned v;
  asm volatile("ld.acquire.gpu.global.u32 %0, [%1];" : "=r"(v) : "l"(p) : "memory");
  return v;
}
__device__ __forceinline__ void wg_fence() { asm volatile("wgmma.fence.sync.aligned;" ::: "memory"); }
__device__ __forceinline__ void wg_commit() { asm volatile("wgmma.commit_group.sync.aligned;" ::: "memory"); }
template <int N> __device__ __forceinline__ void wg_wait() { asm volatile("wgmma.wait_group.sync.aligned %0;" ::"n"(N) : "memory"); }
template <int N> __device__ __forceinline__ void fence_regs(float (&d)[N]) {
#pragma unroll
  for (int i = 0; i < N; i++) asm volatile("" : "+f"(d[i])::"memory");
}
template <int N> __device__ __forceinline__ void fence_regs(uint32_t (&d)[N]) {
#pragma unroll
  for (int i = 0; i < N; i++) asm volatile("" : "+r"(d[i])::"memory");
}
template <int N> __device__ __forceinline__ void pin_regs(const uint32_t* d, uint32_t never, uint32_t addr) {
#pragma unroll
  for (int i = 0; i < N; i += 4)
    asm volatile("{\n.reg .pred p;\nsetp.ne.u32 p, %5, 0;\n@p st.shared.v4.b32 [%0], {%1, %2, %3, %4};\n}\n"
                 ::"r"(addr), "r"(d[i]), "r"(d[i + 1]), "r"(d[i + 2]), "r"(d[i + 3]), "r"(never) : "memory");
}
__device__ __forceinline__ uint32_t pack_bf16(float lo, float hi) {
  uint32_t r;
  asm("cvt.rn.bf16x2.f32 %0, %1, %2;" : "=r"(r) : "f"(hi), "f"(lo));
  return r;
}
__device__ __forceinline__ float ex2(float x) {
  float r;
  asm("ex2.approx.ftz.f32 %0, %1;" : "=f"(r) : "f"(x));
  return r;
}
__device__ __forceinline__ float rcp(float x) {
  float r;
  asm("rcp.approx.ftz.f32 %0, %1;" : "=f"(r) : "f"(x));
  return r;
}
__device__ __forceinline__ uint64_t make_desc(uint32_t addr, uint32_t lbo, uint32_t sbo) {
  return (uint64_t)((addr & 0x3FFFFu) >> 4) | ((uint64_t)(lbo >> 4) << 16) | ((uint64_t)(sbo >> 4) << 32) | (1ull << 62);
}

__device__ __forceinline__ void wgmma_n192_ss_tb(float (&d)[96], uint64_t da, uint64_t db, int scale_d) {
  asm volatile("{\n.reg .pred p;\nsetp.ne.b32 p, %98, 0;\n"
    "wgmma.mma_async.sync.aligned.m64n192k16.f32.bf16.bf16 "
    "{%0, %1, %2, %3, %4, %5, %6, %7, %8, %9, %10, %11, %12, %13, %14, %15, %16, %17, %18, %19, %20, %21, %22, %23, %24, %25, %26, %27, %28, %29, %30, %31, %32, %33, %34, %35, %36, %37, %38, %39, %40, %41, %42, %43, %44, %45, %46, %47, %48, %49, %50, %51, %52, %53, %54, %55, %56, %57, %58, %59, %60, %61, %62, %63, %64, %65, %66, %67, %68, %69, %70, %71, %72, %73, %74, %75, %76, %77, %78, %79, %80, %81, %82, %83, %84, %85, %86, %87, %88, %89, %90, %91, %92, %93, %94, %95}, "
    "%96, %97, p, 1, 1, 0, 1;\n}\n"
    : "+f"(d[0]), "+f"(d[1]), "+f"(d[2]), "+f"(d[3]), "+f"(d[4]), "+f"(d[5]), "+f"(d[6]), "+f"(d[7]), "+f"(d[8]), "+f"(d[9]), "+f"(d[10]), "+f"(d[11]), "+f"(d[12]), "+f"(d[13]), "+f"(d[14]), "+f"(d[15]), "+f"(d[16]), "+f"(d[17]), "+f"(d[18]), "+f"(d[19]), "+f"(d[20]), "+f"(d[21]), "+f"(d[22]), "+f"(d[23]), "+f"(d[24]), "+f"(d[25]), "+f"(d[26]), "+f"(d[27]), "+f"(d[28]), "+f"(d[29]), "+f"(d[30]), "+f"(d[31]), "+f"(d[32]), "+f"(d[33]), "+f"(d[34]), "+f"(d[35]), "+f"(d[36]), "+f"(d[37]), "+f"(d[38]), "+f"(d[39]), "+f"(d[40]), "+f"(d[41]), "+f"(d[42]), "+f"(d[43]), "+f"(d[44]), "+f"(d[45]), "+f"(d[46]), "+f"(d[47]), "+f"(d[48]), "+f"(d[49]), "+f"(d[50]), "+f"(d[51]), "+f"(d[52]), "+f"(d[53]), "+f"(d[54]), "+f"(d[55]), "+f"(d[56]), "+f"(d[57]), "+f"(d[58]), "+f"(d[59]), "+f"(d[60]), "+f"(d[61]), "+f"(d[62]), "+f"(d[63]), "+f"(d[64]), "+f"(d[65]), "+f"(d[66]), "+f"(d[67]), "+f"(d[68]), "+f"(d[69]), "+f"(d[70]), "+f"(d[71]), "+f"(d[72]), "+f"(d[73]), "+f"(d[74]), "+f"(d[75]), "+f"(d[76]), "+f"(d[77]), "+f"(d[78]), "+f"(d[79]), "+f"(d[80]), "+f"(d[81]), "+f"(d[82]), "+f"(d[83]), "+f"(d[84]), "+f"(d[85]), "+f"(d[86]), "+f"(d[87]), "+f"(d[88]), "+f"(d[89]), "+f"(d[90]), "+f"(d[91]), "+f"(d[92]), "+f"(d[93]), "+f"(d[94]), "+f"(d[95])
    : "l"(da), "l"(db), "r"(scale_d));
}
__device__ __forceinline__ void wgmma_n96_rs(float (&d)[48], uint32_t a0, uint32_t a1, uint32_t a2, uint32_t a3, uint64_t db, int scale_d) {
  asm volatile("{\n.reg .pred p;\nsetp.ne.b32 p, %53, 0;\n"
    "wgmma.mma_async.sync.aligned.m64n96k16.f32.bf16.bf16 "
    "{%0, %1, %2, %3, %4, %5, %6, %7, %8, %9, %10, %11, %12, %13, %14, %15, %16, %17, %18, %19, %20, %21, %22, %23, %24, %25, %26, %27, %28, %29, %30, %31, %32, %33, %34, %35, %36, %37, %38, %39, %40, %41, %42, %43, %44, %45, %46, %47}, "
    "{%48, %49, %50, %51}, %52, p, 1, 1, 0;\n}\n"
    : "+f"(d[0]), "+f"(d[1]), "+f"(d[2]), "+f"(d[3]), "+f"(d[4]), "+f"(d[5]), "+f"(d[6]), "+f"(d[7]), "+f"(d[8]), "+f"(d[9]), "+f"(d[10]), "+f"(d[11]), "+f"(d[12]), "+f"(d[13]), "+f"(d[14]), "+f"(d[15]), "+f"(d[16]), "+f"(d[17]), "+f"(d[18]), "+f"(d[19]), "+f"(d[20]), "+f"(d[21]), "+f"(d[22]), "+f"(d[23]), "+f"(d[24]), "+f"(d[25]), "+f"(d[26]), "+f"(d[27]), "+f"(d[28]), "+f"(d[29]), "+f"(d[30]), "+f"(d[31]), "+f"(d[32]), "+f"(d[33]), "+f"(d[34]), "+f"(d[35]), "+f"(d[36]), "+f"(d[37]), "+f"(d[38]), "+f"(d[39]), "+f"(d[40]), "+f"(d[41]), "+f"(d[42]), "+f"(d[43]), "+f"(d[44]), "+f"(d[45]), "+f"(d[46]), "+f"(d[47])
    : "r"(a0), "r"(a1), "r"(a2), "r"(a3), "l"(db), "r"(scale_d));
}
__device__ __forceinline__ void wgmma_n64_rs_tb(float (&d)[32], uint32_t a0, uint32_t a1, uint32_t a2, uint32_t a3, uint64_t db, int scale_d) {
  asm volatile("{\n.reg .pred p;\nsetp.ne.b32 p, %37, 0;\n"
    "wgmma.mma_async.sync.aligned.m64n64k16.f32.bf16.bf16 "
    "{%0, %1, %2, %3, %4, %5, %6, %7, %8, %9, %10, %11, %12, %13, %14, %15, %16, %17, %18, %19, %20, %21, %22, %23, %24, %25, %26, %27, %28, %29, %30, %31}, "
    "{%32, %33, %34, %35}, %36, p, 1, 1, 1;\n}\n"
    : "+f"(d[0]), "+f"(d[1]), "+f"(d[2]), "+f"(d[3]), "+f"(d[4]), "+f"(d[5]), "+f"(d[6]), "+f"(d[7]), "+f"(d[8]), "+f"(d[9]), "+f"(d[10]), "+f"(d[11]), "+f"(d[12]), "+f"(d[13]), "+f"(d[14]), "+f"(d[15]), "+f"(d[16]), "+f"(d[17]), "+f"(d[18]), "+f"(d[19]), "+f"(d[20]), "+f"(d[21]), "+f"(d[22]), "+f"(d[23]), "+f"(d[24]), "+f"(d[25]), "+f"(d[26]), "+f"(d[27]), "+f"(d[28]), "+f"(d[29]), "+f"(d[30]), "+f"(d[31])
    : "r"(a0), "r"(a1), "r"(a2), "r"(a3), "l"(db), "r"(scale_d));
}

__device__ __forceinline__ int chunk_of(int i, int off) { const int c = i + off; return c >= 10 ? c - 10 : c; }
__device__ __forceinline__ int pos_of(int i, int c) { return i - (i > chunk_of(c, 6)) - (i > chunk_of(c, 1)); }
__device__ __forceinline__ int index_at(int t, int r, bool fin) { return (r == 0 && (t < 8 || fin)) ? (t ^ 1) : t; }

constexpr int KPOS = 43;
__device__ __forceinline__ void do_item(const Params& P, int i, int p, int tg, int h0, int r, uint32_t dst, uint32_t bar) {
  if (i >= 46) {
    const int h1 = i >= 49;
    tma4d(dst, &P.v[p], (i - 46 - 3 * h1) * 64, 0, h0 + HS * h1, tg * 4, bar);
  } else if (i >= KPOS && i < KPOS + 3) {
    tma4d(dst, &P.k[p], (i - KPOS) * 64, 0, h0 + HS, tg * 4, bar);
  } else if (i >= 20 && i < 23) {
    tma4d(dst, &P.k[p], (i - 20) * 64, 0, h0, tg * 4, bar);
  } else {
    const int hh = i >= 23;
    const int j = i - 23 * hh - 3 * (i >= KPOS);
    const int kc = j >> 1;
    if (!(j & 1)) tma2d_mc(dst + r * 12288, &P.x[p], kc * 64, tg * 192 + r * 96, bar, (uint16_t)3);
    else tma3d(dst, &P.wq[p], 0, kc * 64, (h0 + HS * hh) * 3, bar);
  }
}

struct Ring {
  uint32_t slot, phase;
  __device__ __forceinline__ void advance() {
    if (++slot == NSLOT) { slot = 0; phase ^= 1; }
  }
};

__device__ __forceinline__ void load_tile(uint32_t (&x)[16], uint32_t addr) {
#pragma unroll
  for (int j = 0; j < 4; j++)
    asm volatile("ld.shared.v4.b32 {%0, %1, %2, %3}, [%4];"
                 : "=r"(x[4 * j]), "=r"(x[4 * j + 1]), "=r"(x[4 * j + 2]), "=r"(x[4 * j + 3]) : "r"(addr + j * 2048) : "memory");
}
__device__ __forceinline__ void store_tile(uint32_t addr, const float (&a)[32]) {
#pragma unroll
  for (int j = 0; j < 4; j++)
    asm volatile("st.shared.v4.b32 [%0], {%1, %2, %3, %4};"
                 ::"r"(addr + j * 2048), "r"(pack_bf16(a[8 * j], a[8 * j + 1])), "r"(pack_bf16(a[8 * j + 2], a[8 * j + 3])),
                   "r"(pack_bf16(a[8 * j + 4], a[8 * j + 5])), "r"(pack_bf16(a[8 * j + 6], a[8 * j + 7])) : "memory");
}
__device__ __forceinline__ uint32_t add_bf16x2(uint32_t a, uint32_t b) {
  uint32_t r;
  asm("add.rn.bf16x2 %0, %1, %2;" : "=r"(r) : "r"(a), "r"(b));
  return r;
}
template <int LUT> __device__ __forceinline__ uint32_t lop3(uint32_t a, uint32_t b, uint32_t c) {
  uint32_t r;
  asm("lop3.b32 %0, %1, %2, %3, %4;" : "=r"(r) : "r"(a), "r"(b), "r"(c), "n"(LUT));
  return r;
}
__device__ __forceinline__ uint32_t tile_ok(const uint32_t (&y)[16], uint32_t tm) {
  return (y[0] ^ tm) & (y[4] ^ tm) & (y[8] ^ tm) & (y[12] ^ tm) & 1u;
}
__device__ __forceinline__ void add_tile(float (&a)[32], const uint32_t (&x)[16]) {
#pragma unroll
  for (int j = 0; j < 16; j++) {
    a[2 * j] += __uint_as_float(x[j] << 16);
    a[2 * j + 1] += __uint_as_float(x[j] & 0xffff0000u);
  }
}
__device__ __forceinline__ uint32_t ophys(uint32_t s) { return (0x26057431u >> (4 * s)) & 7u; }

struct Front {
  Ring rg;
  uint32_t sbase, full0, rel0, never;
  int w, lane, hf;
  __device__ __forceinline__ uint32_t tsb() const { return full0 + 512 + w * 128; }
  __device__ __forceinline__ void release(uint32_t s) const { if (lane < 2) mbar_arrive_cluster(rel0 + 8 * s); }
  __device__ __forceinline__ uint32_t next() {
    const uint32_t s = rg.slot;
    mbar_wait(full0 + 8 * s, rg.phase);
    rg.advance();
    return s;
  }
  template <bool FIRST> __device__ __forceinline__ void qchunk(float (&acc)[96], uint32_t& sx, uint32_t& sw) {
    sx = next(); sw = next();
    const uint64_t da = make_desc(sbase + sx * SLOT_BYTES + w * 8192, 16, 1024);
    const uint64_t db = make_desc(sbase + sw * SLOT_BYTES, 8192, 1024);
    wg_fence();
#pragma unroll
    for (int s = 0; s < QMMA; s++) wgmma_n192_ss_tb(acc, da + 2 * s, db + 128 * s, !FIRST || s != 0);
    wg_commit();
  }
  __device__ __forceinline__ void qrest(float (&acc)[96], uint32_t (&qf)[48], uint32_t psx, uint32_t psw, int kc0, int tbase) {
#pragma unroll 1
    for (int kc = kc0; kc < 10; kc++) {
      uint32_t sx, sw;
      qchunk<false>(acc, sx, sw);
      QSTAMP(20 + kc);
      wg_wait<1>(); release(psx); release(psw);
      psx = sx; psw = sw;
    }
    wg_wait<0>();
    fence_regs(acc);
    release(psx); release(psw);
#pragma unroll
    for (int i = 24; i < 48; i++) qf[i] = pack_bf16(acc[2 * i], acc[2 * i + 1]);
    pin_regs<24>(qf + 24, never, full0);
#pragma unroll
    for (int i = 0; i < 24; i++) qf[i] = pack_bf16(acc[2 * i], acc[2 * i + 1]);
    pin_regs<24>(qf, never, full0);
    fence_regs(qf);
  }
  __device__ __forceinline__ void scores(float (&v)[24], const uint32_t (&qf)[48]) {
    float sacc[48];
    uint32_t ks[3];
#pragma unroll
    for (int dc = 0; dc < 3; dc++) {
      ks[dc] = next();
      const uint64_t db = make_desc(sbase + ks[dc] * SLOT_BYTES + w * 6144, 16, 1024);
      wg_fence();
#pragma unroll
      for (int s = 0; s < 4; s++) {
        const int j = dc * 4 + s;
        wgmma_n96_rs(sacc, qf[4 * j], qf[4 * j + 1], qf[4 * j + 2], qf[4 * j + 3], db + 2 * s, j != 0);
      }
    }
    wg_commit();
    wg_wait<0>();
    fence_regs(sacc);
    release(ks[0]); release(ks[1]); release(ks[2]);
#pragma unroll
    for (int i = 0; i < 24; i++) v[i] = hf ? sacc[24 + i] : sacc[i];
    fence_regs(v);
  }
  __device__ __forceinline__ void softmax(uint32_t (&pk)[12], float (&v)[24]) {
    float m0 = v[0], m1 = v[2];
#pragma unroll
    for (int t = 0; t < 6; t++) {
      m0 = fmaxf(m0, fmaxf(v[4 * t], v[4 * t + 1]));
      m1 = fmaxf(m1, fmaxf(v[4 * t + 2], v[4 * t + 3]));
    }
    m0 = fmaxf(m0, __shfl_xor_sync(0xffffffffu, m0, 1));
    m1 = fmaxf(m1, __shfl_xor_sync(0xffffffffu, m1, 1));
    m0 = fmaxf(m0, __shfl_xor_sync(0xffffffffu, m0, 2));
    m1 = fmaxf(m1, __shfl_xor_sync(0xffffffffu, m1, 2));
    const float cs = 0.07216878364870322f * 1.4426950408889634f;
    const float b0 = m0 * cs, b1 = m1 * cs;
    float s0 = 0.f, s1 = 0.f;
#pragma unroll
    for (int t = 0; t < 6; t++) {
      v[4 * t] = ex2(fmaf(v[4 * t], cs, -b0));
      v[4 * t + 1] = ex2(fmaf(v[4 * t + 1], cs, -b0));
      v[4 * t + 2] = ex2(fmaf(v[4 * t + 2], cs, -b1));
      v[4 * t + 3] = ex2(fmaf(v[4 * t + 3], cs, -b1));
      s0 += v[4 * t] + v[4 * t + 1];
      s1 += v[4 * t + 2] + v[4 * t + 3];
    }
    s0 += __shfl_xor_sync(0xffffffffu, s0, 1);
    s1 += __shfl_xor_sync(0xffffffffu, s1, 1);
    s0 += __shfl_xor_sync(0xffffffffu, s0, 2);
    s1 += __shfl_xor_sync(0xffffffffu, s1, 2);
    const float r0 = rcp(s0), r1 = rcp(s1);
#pragma unroll
    for (int t = 0; t < 6; t++) {
      pk[2 * t] = pack_bf16(v[4 * t] * r0, v[4 * t + 1] * r0);
      pk[2 * t + 1] = pack_bf16(v[4 * t + 2] * r1, v[4 * t + 3] * r1);
    }
    pin_regs<12>(pk, never, full0);
    fence_regs(pk);
  }
  __device__ __forceinline__ void expand(uint32_t (&pa)[24], uint32_t (&pk)[12]) {
    fence_regs(pk);
#pragma unroll
    for (int i = 0; i < 12; i++) {
      pa[i] = hf ? 0u : pk[i];
      pa[12 + i] = hf ? pk[i] : 0u;
    }
    fence_regs(pa);
  }
  __device__ __forceinline__ void pv(float (&oa)[32], const uint32_t (&pa)[24], int s, int parity) {
    mbar_wait(full0 + 8 * s, parity);
    const uint64_t db = make_desc(sbase + s * SLOT_BYTES + w * 6144, 16, 1024);
    wg_fence();
#pragma unroll
    for (int j = 0; j < 6; j++) wgmma_n64_rs_tb(oa, pa[4 * j], pa[4 * j + 1], pa[4 * j + 2], pa[4 * j + 3], db + 128 * j, j != 0);
  }
  __device__ __forceinline__ void pack16(uint32_t* o, const float (&oa)[32]) {
#pragma unroll
    for (int i = 0; i < 16; i++) o[i] = pack_bf16(oa[2 * i], oa[2 * i + 1]);
    pin_regs<16>(o, never, full0);
  }
  __device__ __forceinline__ void early(float (&a)[32], const uint32_t (&o0)[48], int t) {
    mbar_wait(full0 + FULLO + 16 * t, 0);
    const uint64_t db = make_desc(sbase + (4 + t) * SLOT_BYTES, 16, 1024);
    wg_fence();
#pragma unroll
    for (int j = 0; j < 12; j++)
      wgmma_n64_rs_tb(a, o0[4 * j], o0[4 * j + 1], o0[4 * j + 2], o0[4 * j + 3], db + 128 * j, j != 0);
    wg_commit();
  }
  __device__ __forceinline__ void park(float (&a)[32], int t) {
    fence_regs(a);
    if (lane == 0) mbar_arrive(full0 + EMPTYE + 8 * (t + 1));
    mbar_wait(full0 + EMPTYE + 8 * t, 0);
    uint32_t tid;
    asm volatile("mov.u32 %0, %%tid.x;" : "=r"(tid));
    store_tile(sbase + ophys(2 * t) * SLOT_BYTES + (tid >> 7) * XBUF_BYTES + (tid & 127) * 16, a);
  }
  __device__ __forceinline__ void run(uint32_t (&o0)[48], uint32_t (&o1)[48]) {
    uint32_t pk[12], pa[24];
    float v[24];
    {
      uint32_t qf[48];
      {
        float acc[96];
        uint32_t sx, sw;
        qchunk<true>(acc, sx, sw);
        { const int tbase = 1; (void)tbase; QSTAMP(20); }
        qrest(acc, qf, sx, sw, 1, 1);
      }
      TSTAMP(1);
      scores(v, qf);
      TSTAMP(2);
    }
    {
      uint32_t qf[48];
      {
        float acc[96];
        uint32_t ax, aw, bx, bw;
        qchunk<true>(acc, ax, aw);
        qchunk<false>(acc, bx, bw);
        softmax(pk, v);
        TSTAMP(3);
        wg_wait<1>(); release(ax); release(aw);
        qrest(acc, qf, bx, bw, 2, 4);
      }
      TSTAMP(4);
      scores(v, qf);
      TSTAMP(5);
    }
    {
      float oa[32], ob[32], oc[32];
      expand(pa, pk);
      pv(oa, pa, 1, 1); pv(ob, pa, 2, 1); pv(oc, pa, 3, 1);
      wg_commit();
      XSTAMP(20);
      softmax(pk, v);
      XSTAMP(21);
      wg_wait<0>();
      fence_regs(oa); fence_regs(ob); fence_regs(oc);
      XSTAMP(22);
      release(2); release(3);
      if (lane == 0) mbar_arrive(full0 + EMPTYE);
      pack16(o0, oa); pack16(o0 + 16, ob); pack16(o0 + 32, oc);
      fence_regs(o0);
    }
    {
      float oa[32], ob[32];
      early(oa, o0, 0);
      early(ob, o0, 1);
      XSTAMP(23);
      wg_wait<1>(); park(oa, 0);
      early(oa, o0, 2);
      wg_wait<1>(); park(ob, 1);
      early(ob, o0, 3);
      XSTAMP(24);
      wg_wait<1>(); park(oa, 2);
      wg_wait<0>(); park(ob, 3);
      XSTAMP(25);
      fence_regs(o0);
#pragma unroll
      for (int i = 0; i < 12; i++) o0[i] += never;
      fence_regs(o0);
      expand(pa, pk);
      pv(oa, pa, 8, 1);
      pv(ob, pa, 0, 0);
      wg_commit();
      XSTAMP(26);
      wg_wait<0>();
      fence_regs(oa); fence_regs(ob);
      XSTAMP(27);
      release(8); release(0);
      pack16(o1, oa); pack16(o1 + 16, ob);
      float oc[32];
      pv(oc, pa, 2, 0);
      wg_commit();
      XSTAMP(28);
      wg_wait<0>();
      fence_regs(oc);
      release(2);
      pack16(o1 + 32, oc);
    }
    TSTAMP(6);
  }
};

__device__ __forceinline__ uint32_t oslot_addr(uint32_t sbase, uint32_t s) { return sbase + ophys(s) * SLOT_BYTES; }
template <bool EARLY>
__device__ __forceinline__ void oproj_chunk(float (&a)[32], const uint32_t (&o0)[48], const uint32_t (&o1)[48], int t, uint32_t toff,
                                            uint32_t sbase, uint32_t fullo0, uint32_t emptyo0, int lane, int w, int wnext, bool pass) {
  const uint32_t s0 = (2 * t) & 7, s1 = s0 + 1, ph = (t >> 2) & 1;
  if (EARLY) {
    uint32_t x[16];
    load_tile(x, oslot_addr(sbase, s0) + toff);
#pragma unroll
    for (int j = 0; j < 16; j++) {
      a[2 * j] = __uint_as_float(x[j] << 16);
      a[2 * j + 1] = __uint_as_float(x[j] & 0xffff0000u);
    }
    fence_regs(a);
    if (!(t & 1)) {
      __syncwarp();
      if (lane == 0) mbar_arrive(emptyo0 + 8 * s0);
    }
  } else {
    mbar_wait(fullo0 + 8 * s0, ph);
  }
  mbar_wait(fullo0 + 8 * s1, ph);
  asm volatile("bar.sync %0, 256;" ::"r"(1 + w) : "memory");
  wg_fence();
  if (!EARLY) {
    const uint64_t db = make_desc(oslot_addr(sbase, s0), 16, 1024);
#pragma unroll
    for (int j = 0; j < 12; j++)
      wgmma_n64_rs_tb(a, o0[4 * j], o0[4 * j + 1], o0[4 * j + 2], o0[4 * j + 3], db + 128 * j, j != 0);
    wg_commit();
  }
  {
    const uint64_t db = make_desc(oslot_addr(sbase, s1), 16, 1024);
#pragma unroll
    for (int j = 0; j < 12; j++) {
      wgmma_n64_rs_tb(a, o1[4 * j], o1[4 * j + 1], o1[4 * j + 2], o1[4 * j + 3], db + 128 * j, 1);
      if (j == TOKEN_AT && pass) asm volatile("bar.arrive %0, 256;" ::"r"(1 + wnext) : "memory");
    }
    wg_commit();
  }
  if (!EARLY) {
    wg_wait<1>();
    if (lane == 0) mbar_arrive(emptyo0 + 8 * s0);
  }
  wg_wait<0>();
  fence_regs(a);
  if (lane == 0) mbar_arrive(emptyo0 + 8 * s1);
}

__global__ void __cluster_dims__(2, 1, 1) __launch_bounds__(NTHREADS, 1)
fused_kernel(const __grid_constant__ Params P, __nv_bfloat16* __restrict__ out) {
  extern __shared__ uint8_t smem_raw[];
  const uint32_t sbase = (smem_u32(smem_raw) + 1023u) & ~1023u;
  const uint32_t full0 = sbase + BAR_OFF;
  const uint32_t empty0 = full0 + 72;
  const uint32_t xfull0 = full0 + 144;
  const uint32_t xempty0 = full0 + 168;
  const uint32_t fullo0 = full0 + FULLO;
  const uint32_t emptyo0 = full0 + 256;
  const uint32_t ready0 = full0 + 400;
  const uint32_t eready = full0 + 344;
  const uint32_t epoch_s = full0 + 352;
  const uint32_t emptye0 = full0 + EMPTYE;

  const int tid = threadIdx.x, lane = tid & 31;
  const int warp = __shfl_sync(0xffffffffu, tid >> 5, 0);
  auto tsb = [&]() { return full0 + 512 + (warp >> 2) * 128; };
  const int bid = blockIdx.x;
  const int hp = bid & 15, tg = (bid >> 4) & 3, p = bid >> 6;
  const int r = hp & 1;
  const int h0 = hp * HM;
  const int grp = p * 4 + tg;
  const int off = (hp >> 1) + (hp >> 3);
  const bool fin = r == 1 || off == 0 || off == 5;

  if (tid == 384) {
    asm volatile("prefetch.tensormap [%0];" ::"l"(&P.x[p]) : "memory");
    asm volatile("prefetch.tensormap [%0];" ::"l"(&P.wq[p]) : "memory");
#pragma unroll
    for (int i = 0; i < NSLOT; i++) mbar_init(full0 + 8 * i, 1);
    asm volatile("fence.mbarrier_init.release.cluster;" ::: "memory");
  }
  if (tid == 416) {
    for (int i = 0; i < NSLOT; i++) mbar_init(empty0 + 8 * i, 24);
    for (int i = 0; i < 3; i++) { mbar_init(xfull0 + 8 * i, 1); mbar_init(xempty0 + 8 * i, 4); }
    for (int i = 0; i < 12; i++) mbar_init(ready0 + 8 * i, 4);
    mbar_init(eready, 3);
    for (int i = 0; i < 5; i++) mbar_init(emptye0 + 8 * i, 12);
    for (int i = 0; i < NSLOT_O; i++) { mbar_init(fullo0 + 8 * i, 1); mbar_init(emptyo0 + 8 * i, 12); }
    asm volatile("fence.mbarrier_init.release.cluster;" ::: "memory");
    for (int i = 0; i < 3; i++) mbar_expect_tx(xfull0 + 8 * i, XBUF_BYTES);
  }
  __syncwarp();
  asm volatile("barrier.cluster.arrive.relaxed.aligned;" ::: "memory");
  if (tid == 384) {
#pragma unroll
    for (int i = 0; i < NSLOT; i++) {
      mbar_expect_tx(full0 + 8 * i, SLOT_BYTES);
      if (i & 1) {
        tma3d(sbase + i * SLOT_BYTES, &P.wq[p], 0, (i >> 1) * 64, h0 * 3, full0 + 8 * i);
      } else {
        tma2d(sbase + i * SLOT_BYTES, &P.x[p], (i >> 1) * 64, tg * 192, full0 + 8 * i);
        tma2d(sbase + i * SLOT_BYTES + 12288, &P.x[p], (i >> 1) * 64, tg * 192 + 96, full0 + 8 * i);
      }
    }
  }
  if (tid == 416) {
    asm volatile("prefetch.tensormap [%0];" ::"l"(&P.k[p]) : "memory");
    asm volatile("prefetch.tensormap [%0];" ::"l"(&P.v[p]) : "memory");
    asm volatile("prefetch.tensormap [%0];" ::"l"(&P.wo[p]) : "memory");
  }
  __syncwarp();
  asm volatile("barrier.cluster.wait.aligned;" ::: "memory");

  if (warp >= 12) {
    asm volatile("setmaxnreg.dec.sync.aligned.u32 32;");
    if (warp == 12) {
      if (lane == 0) {
        TSTAMP(3); CSTAMP(28);
        uint32_t slot = 0, phase = 1;
#pragma unroll 1
        for (int i = NSLOT; i < 49; i++) {
          mbar_wait(empty0 + 8 * slot, phase ^ 1);
          mbar_expect_tx(full0 + 8 * slot, SLOT_BYTES);
          do_item(P, i, p, tg, h0, r, sbase + slot * SLOT_BYTES, full0 + 8 * slot);
          if (++slot == NSLOT) { slot = 0; phase ^= 1; }
        }
        TSTAMP(2); CSTAMP(29);
#pragma unroll 1
        for (int e = 0; e < 23; e++) {
          int j = e - 3;
          if (e < 11) {
            slot = (uint32_t)(0x20732087654ull >> (4 * e)) & 15u;
            if (e == 8) mbar_wait(emptye0 + 32, 0);
            else mbar_wait(empty0 + 8 * slot, e >= 5 && e < 8);
            if (e >= 4 && e < 7) {
              mbar_expect_tx(full0 + 8 * slot, SLOT_BYTES);
              do_item(P, 45 + e, p, tg, h0, r, sbase + slot * SLOT_BYTES, full0 + 8 * slot);
              continue;
            }
            j = e < 4 ? 2 * e : 2 * e - 13;
          } else {
            slot = ophys(j & 7);
            mbar_wait(emptyo0 + 8 * (j & 7), ((j >> 3) & 1) ^ 1);
            if (j < 16) asm volatile("fence.proxy.async.shared::cta;" ::: "memory");
          }
          mbar_expect_tx(fullo0 + 8 * (j & 7), SLOT_BYTES);
          tma2d(sbase + slot * SLOT_BYTES, &P.wo[p], chunk_of(index_at(j >> 1, r, fin), off) * 64, (h0 + HS * (j & 1)) * 192, fullo0 + 8 * (j & 7));
        }
        TSTAMP(1); CSTAMP(30);
        if (fin) {
          const uint4* src = g_part + (size_t)(grp * 10 + chunk_of(8 + r, off)) * 7 * (SLOT_BYTES / 16);
#pragma unroll 1
          for (int g = 0; g < 4; g++) {
            mbar_wait(emptyo0 + 8 * (4 + g), 1);
            if (g == 0) mbar_expect_tx(fullo0 + 8 * 4, 4 * SLOT_BYTES);
            TSTAMP(4 + g);
            asm volatile("cp.async.bulk.shared::cluster.global.mbarrier::complete_tx::bytes [%0], [%1], %2, [%3];"
                         ::"r"(oslot_addr(sbase, 4 + g)), "l"(src + g * (SLOT_BYTES / 16)), "r"(SLOT_BYTES), "r"(fullo0 + 8 * 4) : "memory");
          }
        }
      }
    } else {
      const int w = warp - 13;
      unsigned epoch;
      asm volatile("ld.global.cg.u32 %0, [%1];" : "=r"(epoch) : "l"(&g_epoch[grp]));
      auto post_epoch = [&]() {
        if (lane == 0) {
          asm volatile("st.shared.u32 [%0], %1;" ::"r"(epoch_s), "r"(epoch) : "memory");
          mbar_arrive(eready);
        }
      };
      {
        uint32_t sink = sbase + SINK_OFF + (w * 16 + lane) * 16;
        int un = 0;
#pragma unroll 1
        for (int ph = 0; ph < 5; ph++) {
          const char* q;
          int nb = 4, nt = 3;
          uint32_t sb = 589824;
          if (ph == 1) {
            q = P.wqp[p] + (size_t)(lane * 4 + tg) * 12288 + (h0 + HS) * 384 + w * 128;
            nb = 10; nt = 1; sb = 786432;
          } else {
            q = (ph < 3 ? P.kp[p] : P.vp[p]) + (size_t)(tg * 128 + h0 + HS * (ph == 2 || ph == 4)) * 18432 + (w * 16 + lane) * 128;
          }
#pragma unroll 1
          for (int b = 0; b < nb; b++, q += sb) {
            if (mbar_test(emptye0 + 32, 0)) break;
#pragma unroll 1
            for (int t = 0; t < nt; t++) {
              if (ph < PF_NW) asm volatile("cp.async.wait_group %0;" ::"n"(PF_WIN1 - 1) : "memory");
              else asm volatile("cp.async.wait_group %0;" ::"n"(PF_WIN - 1) : "memory");
              if (!(un & 1)) { PSTAMP(un >> 1); }
              if (lane < 16)
                asm volatile("cp.async.cg.shared.global.L2::128B [%0], [%1], 16;" ::"r"(sink + (un % PF_WIN) * 768), "l"(q + t * 6144) : "memory");
              asm volatile("cp.async.commit_group;" ::: "memory");
              un++;
            }
          }
          if (ph == 0) post_epoch();
        }
        asm volatile("cp.async.wait_all;" ::: "memory");
      }
      if (lane == 0) {
#pragma unroll 1
        for (int k = 0; k < 4; k++) {
          const int c = chunk_of(2 * k + r, off), pos = pos_of(2 * k + r, c);
          uint4* dst = g_part + (size_t)((grp * 10 + c) * 7 + pos) * (SLOT_BYTES / 16) + w * 512;
          const uint32_t src = (k < 2 ? oslot_addr(sbase, 4 * k + 2) : sbase + XBUF_OFF) + w * XBUF_BYTES;
          mbar_wait(ready0 + 24 * k + 8 * w, 0);
          asm volatile("fence.proxy.async.shared::cta;" ::: "memory");
          asm volatile("cp.async.bulk.global.shared::cta.bulk_group [%0], [%1], %2;" ::"l"(dst), "r"(src), "r"(XBUF_BYTES) : "memory");
          asm volatile("cp.async.bulk.commit_group;" ::: "memory");
          asm volatile("cp.async.bulk.wait_group.read 0;" ::: "memory");
          if (k < 2) {
            asm volatile("mbarrier.arrive.shared::cta.b64 _, [%0], 4;" ::"r"(emptyo0 + 8 * (4 * k + 2)) : "memory");
          } else {
            mbar_expect_tx(xfull0 + 8 * w, XBUF_BYTES);
            asm volatile("mbarrier.arrive.shared::cluster.b64 _, [%0], 4;" ::"r"(mapa(xempty0 + 8 * w, r ^ 1)) : "memory");
          }
        }
      }
    }
    __syncwarp();
    TDUMP();
  } else {
    asm volatile("setmaxnreg.inc.sync.aligned.u32 160;");
    const int w = warp >> 2;
    const int hf = warp / 3 - w;
    uint32_t o0[48], o1[48];
    const uint32_t never = (out == nullptr);
    {
      Front f{{0, 0}, sbase, full0, mapa(empty0, lane & 1), never, w, lane, hf};
      f.run(o0, o1);
    }
#pragma unroll
    for (int i = 0; i < 12; i++) o0[i] ^= never;
    fence_regs(o0); fence_regs(o1);

    const int wt = tid & 127;
    const int wnext = w == 2 ? 0 : w + 1;
    if (w == 2) asm volatile("bar.arrive 1, 256;" ::: "memory");
    const uint32_t xb = sbase + XBUF_OFF + w * XBUF_BYTES + wt * 16;
    mbar_wait(eready, 0);
    uint32_t tag;
    asm volatile("ld.shared.u32 %0, [%1];" : "=r"(tag) : "r"(epoch_s) : "memory");
    tag = __shfl_sync(0xffffffffu, ~tag & 1u, 0);
    float a[32];
    auto epilogue = [&](int t) {
      const int k = t >> 1;
      const int ci = index_at(t, r, fin);
      if ((ci & 1) != r) {
        if (k == 0) mbar_wait(empty0 + 8 * 8, 1);
        else mbar_wait(xempty0 + 8 * w, (k - 1) & 1);
        FSTAMP(20);
        const uint32_t rxb = mapa(xb, r ^ 1);
        const uint32_t rbar = mapa(xfull0 + 8 * w, r ^ 1);
#pragma unroll
        for (int j = 0; j < 4; j++)
          asm volatile("st.async.weak.shared::cluster.mbarrier::complete_tx::bytes.v4.b32 [%0], {%1, %2, %3, %4}, [%5];"
                       ::"r"(rxb + j * 2048), "r"(pack_bf16(a[8 * j], a[8 * j + 1])), "r"(pack_bf16(a[8 * j + 2], a[8 * j + 3])),
                         "r"(pack_bf16(a[8 * j + 4], a[8 * j + 5])), "r"(pack_bf16(a[8 * j + 6], a[8 * j + 7])), "r"(rbar) : "memory");
      } else {
        uint32_t z[16];
#pragma unroll
        for (int j = 0; j < 16; j++) z[j] = pack_bf16(a[2 * j], a[2 * j + 1]);
        mbar_wait(xfull0 + 8 * w, k & 1);
        FSTAMP(20);
        {
          uint32_t x[16];
          load_tile(x, xb);
#pragma unroll
          for (int j = 0; j < 16; j++) z[j] = add_bf16x2(z[j], x[j]);
#pragma unroll
          for (int j = 0; j < 16; j += 4) z[j] = (z[j] & ~1u) | tag;
        }
        if (k < 2) {
          if (wt == 0) mbar_expect_tx(xfull0 + 8 * w, XBUF_BYTES);
          fence_regs(z);
          __syncwarp();
          if (lane == 0) mbar_arrive_cluster(mapa(xempty0 + 8 * w, r ^ 1));
        }
        FSTAMP(21);
        if (k < 4) {
          const uint32_t st = k < 2 ? oslot_addr(sbase, 2 * t) + w * XBUF_BYTES + wt * 16 : xb;
#pragma unroll
          for (int j = 0; j < 4; j++)
            asm volatile("st.shared.v4.b32 [%0], {%1, %2, %3, %4};"
                         ::"r"(st + j * 2048), "r"(z[4 * j]), "r"(z[4 * j + 1]), "r"(z[4 * j + 2]), "r"(z[4 * j + 3]) : "memory");
          __syncwarp();
          if (lane == 0) mbar_arrive(ready0 + 24 * k + 8 * w);
        } else {
          const int c = chunk_of(ci, off), pos = pos_of(ci, c);
          uint4* dst = g_part + (size_t)((grp * 10 + c) * 7 + pos) * (SLOT_BYTES / 16) + w * 512 + wt;
#pragma unroll
          for (int j = 0; j < 4; j++)
            asm volatile("st.relaxed.gpu.global.v4.b32 [%0], {%1, %2, %3, %4};"
                         ::"l"(dst + j * 128), "r"(z[4 * j]), "r"(z[4 * j + 1]), "r"(z[4 * j + 2]), "r"(z[4 * j + 3]) : "memory");
        }
        FSTAMP(22);
      }
      ESTAMP(20 + t);
      FSTAMP(23);
    };
    auto finalize = [&]() {
      const int c = chunk_of(8 + r, off);
      TSTAMP(7);
      const uint4* tiles = g_part + (size_t)(grp * 10 + c) * 7 * (SLOT_BYTES / 16) + w * 512 + wt;
      auto load_g = [&](uint32_t (&y)[16], int q) {
#pragma unroll
        for (int j = 0; j < 4; j++)
          asm volatile("ld.relaxed.gpu.global.v4.b32 {%0, %1, %2, %3}, [%4];"
                       : "=r"(y[4 * j]), "=r"(y[4 * j + 1]), "=r"(y[4 * j + 2]), "=r"(y[4 * j + 3])
                       : "l"(tiles + q * (SLOT_BYTES / 16) + j * 128) : "memory");
      };
      const uint32_t toff = w * XBUF_BYTES + wt * 16;
      const uint32_t tm = tag - 1u;
      const uint32_t t0 = clk32();
      auto settle = [&](uint32_t (&y)[16], int q) {
        while (true) {
          if (tile_ok(y, tm) || clk32() - t0 > SPIN_LIMIT) break;
          load_g(y, q);
        }
        add_tile(a, y);

      };
      mbar_wait(fullo0 + 8 * 4, 0);
      uint32_t ok = 1u;
#pragma unroll
      for (int j = 0; j < 4; j++) {
        uint32_t x[4][4];
#pragma unroll
        for (int q = 0; q < 4; q++)
          asm volatile("ld.shared.v4.b32 {%0, %1, %2, %3}, [%4];"
                       : "=r"(x[q][0]), "=r"(x[q][1]), "=r"(x[q][2]), "=r"(x[q][3]) : "r"(oslot_addr(sbase, 4 + q) + toff + j * 2048) : "memory");
        ok = lop3<0x80>(ok, lop3<0x42>(x[0][0], x[1][0], tm), lop3<0x42>(x[2][0], x[3][0], tm));
#pragma unroll
        for (int i = 0; i < 4; i++) {
          const uint32_t u = add_bf16x2(x[0][i], x[1][i]), v = add_bf16x2(x[2][i], x[3][i]);
          a[8 * j + 2 * i] = __uint_as_float(u << 16) + __uint_as_float(v << 16);
          a[8 * j + 2 * i + 1] = __uint_as_float(u & 0xffff0000u) + __uint_as_float(v & 0xffff0000u);
        }
      }
      if (!ok) {
#pragma unroll
        for (int j = 0; j < 32; j++) a[j] = 0.f;
#pragma unroll 1
        for (int q = 0; q < 4; q++) {
          uint32_t x[16];
          load_g(x, q);
          settle(x, q);
        }
      }
      fence_regs(a);
      TSTAMP(30);
      mbar_wait(fullo0 + 8 * 2, 0);
      mbar_wait(fullo0 + 8 * 3, 0);
      asm volatile("bar.sync %0, 256;" ::"r"(1 + w) : "memory");
      wg_fence();
      {
        const uint64_t db = make_desc(oslot_addr(sbase, 2), 16, 1024);
#pragma unroll
        for (int j = 0; j < 12; j++) wgmma_n64_rs_tb(a, o0[4 * j], o0[4 * j + 1], o0[4 * j + 2], o0[4 * j + 3], db + 128 * j, 1);
        wg_commit();
      }
      {
        const uint64_t db = make_desc(oslot_addr(sbase, 3), 16, 1024);
#pragma unroll
        for (int j = 0; j < 12; j++) {
          wgmma_n64_rs_tb(a, o1[4 * j], o1[4 * j + 1], o1[4 * j + 2], o1[4 * j + 3], db + 128 * j, 1);
          if (j == TOKEN_AT && w < 2) asm volatile("bar.arrive %0, 256;" ::"r"(1 + wnext) : "memory");
        }
        wg_commit();
      }
      {
        uint32_t x[16], y0[16], y1[16], y2[16];
        wg_wait<1>();
        load_g(y0, 4); load_g(y1, 5); load_g(y2, 6);
        wg_wait<0>();
        fence_regs(a);
        TSTAMP(19);
        mbar_wait(xfull0 + 8 * w, 0); load_tile(x, xb);
        add_tile(a, x);
        fence_regs(a);
        TSTAMP(31);
        settle(y0, 4); settle(y1, 5); settle(y2, 6);
      }
      TSTAMP(8);
      const int row = tg * 192 + w * 64 + (wt >> 5) * 16 + ((wt >> 2) & 7);
      uint4* d0 = reinterpret_cast<uint4*>(out + (size_t)row * 1280 + p * 640 + c * 64 + (wt & 3) * 8);
      const bool b0 = wt & 1, b1 = wt & 2;
      __syncwarp();
#pragma unroll
      for (int u = 0; u < 4; u++) {
        uint32_t x[4];
#pragma unroll
        for (int i = 0; i < 4; i++) {
          const int j = (u & 1) * 4 + i;
          x[i] = pack_bf16(a[4 * j + (u >> 1) * 2], a[4 * j + (u >> 1) * 2 + 1]);
        }
        uint32_t v;
        v = __shfl_xor_sync(0xffffffffu, b0 ? x[0] : x[1], 1); if (b0) x[0] = v; else x[1] = v;
        v = __shfl_xor_sync(0xffffffffu, b0 ? x[2] : x[3], 1); if (b0) x[2] = v; else x[3] = v;
        v = __shfl_xor_sync(0xffffffffu, b1 ? x[0] : x[2], 2); if (b1) x[0] = v; else x[2] = v;
        v = __shfl_xor_sync(0xffffffffu, b1 ? x[1] : x[3], 2); if (b1) x[1] = v; else x[3] = v;
        d0[(u & 1) * 4 + (u >> 1) * 8 * 160] = make_uint4(x[0], x[1], x[2], x[3]);
      }
      if (hp == 1 && tid == 0) asm volatile("red.relaxed.gpu.global.add.u32 [%0], 1;" ::"l"(&g_epoch[grp]) : "memory");
    };
#pragma unroll 1
    for (int t = 0; t < 4; t++) {
      oproj_chunk<true>(a, o0, o1, t, w * XBUF_BYTES + wt * 16, sbase, fullo0, emptyo0, lane, w, wnext, true);
      TSTAMP(10 + t);
      epilogue(t);
    }
#pragma unroll 1
    for (int t = 4; t < 10; t++) {
      if (t == 9 && fin) { finalize(); break; }
      oproj_chunk<false>(a, o0, o1, t, 0, sbase, fullo0, emptyo0, lane, w, wnext, t < 9 || w < 2);
      TSTAMP(10 + t);
      epilogue(t);
    }
    TSTAMP(9);
    __syncwarp();
    TDUMP();
  }
}

typedef CUresult (*EncodeFn)(CUtensorMap*, CUtensorMapDataType, cuuint32_t, void*, const cuuint64_t*, const cuuint64_t*,
                             const cuuint32_t*, const cuuint32_t*, CUtensorMapInterleave, CUtensorMapSwizzle,
                             CUtensorMapL2promotion, CUtensorMapFloatOOBfill);

static void encode(EncodeFn fn, CUtensorMap* m, const void* ptr, int rank, const cuuint64_t* dims, const cuuint64_t* strides,
                   const cuuint32_t* box) {
  cuuint32_t es[5] = {1, 1, 1, 1, 1};
  fn(m, CU_TENSOR_MAP_DATA_TYPE_BFLOAT16, (cuuint32_t)rank, const_cast<void*>(ptr), dims, strides, box, es,
     CU_TENSOR_MAP_INTERLEAVE_NONE, CU_TENSOR_MAP_SWIZZLE_128B, CU_TENSOR_MAP_L2_PROMOTION_L2_256B,
     CU_TENSOR_MAP_FLOAT_OOB_FILL_NONE);
}

}

extern "C" void kernel_launch(void* const* d_in, const int* in_sizes, int n_in, void* d_out, int out_size) {
  using namespace fk;
  static Params params;
  static const void* cached[10] = {nullptr};
  static EncodeFn fn = nullptr;
  if (!fn) {
    void* f = nullptr;
    cudaDriverEntryPointQueryResult st;
    cudaGetDriverEntryPoint("cuTensorMapEncodeTiled", &f, cudaEnableDefault, &st);
    fn = (EncodeFn)f;
    cudaFuncSetAttribute(fused_kernel, cudaFuncAttributeMaxDynamicSharedMemorySize, SMEM_BYTES);
  }
  bool same = true;
  for (int i = 0; i < 10; i++) same = same && (cached[i] == d_in[i]);
  if (!same) {
    for (int p = 0; p < 2; p++) {
      const void* x = d_in[5 * p + 0];
      const void* k = d_in[5 * p + 1];
      const void* v = d_in[5 * p + 2];
      const void* wq = d_in[5 * p + 3];
      const void* wo = d_in[5 * p + 4];
      params.kp[p] = (const char*)k; params.vp[p] = (const char*)v;
      params.wqp[p] = (const char*)wq; params.wop[p] = (const char*)wo;
      {
        cuuint64_t d[2] = {640, 768}, s[1] = {1280};
        cuuint32_t b[2] = {64, 96};
        encode(fn, &params.x[p], x, 2, d, s, b);
      }
      {
        cuuint64_t d[3] = {64, 640, 96}, s[2] = {12288, 128};
        cuuint32_t b[3] = {64, 64, 3};
        encode(fn, &params.wq[p], wq, 3, d, s, b);
      }
      {
        cuuint64_t d[4] = {192, 48, 32, 16}, s[3] = {384, 18432, 589824};
        cuuint32_t b[4] = {64, 48, 1, 4};
        encode(fn, &params.k[p], k, 4, d, s, b);
        encode(fn, &params.v[p], v, 4, d, s, b);
      }
      {
        cuuint64_t d[2] = {640, 6144}, s[1] = {1280};
        cuuint32_t b[2] = {64, 192};
        encode(fn, &params.wo[p], wo, 2, d, s, b);
      }
    }
    for (int i = 0; i < 10; i++) cached[i] = d_in[i];
  }
  fused_kernel<<<128, NTHREADS, SMEM_BYTES>>>(params, (__nv_bfloat16*)d_out);
}
```

```cpp
#include <cuda_runtime.h>
#include <cuda_bf16.h>
#include <cuda.h>
#include <stdint.h>

#define PF_ON 1
#define PF_WIN 4
#define PF_WIN1 4
#define PF_WIN0 3
#define FDELAY 500
#define FDELAY_C 1
#define PRE3 1
#define YFIRST 1
#define PACE 485
#define PF_TRIG 3
#define PF0_FROM 5
#define PF_NW 2
#define PF0 1
#define QMMA 4
#define TOKEN_AT 8
#define SPIN_LIMIT (1u << 27)

namespace fk {

#define HEADMAP 0
constexpr int HM = HEADMAP ? 1 : 2, HS = HEADMAP ? 16 : 1;
constexpr int SLOT_BYTES = 24576;
constexpr int NSLOT = 9;
constexpr int NSLOT_O = 8;
constexpr int XBUF_BYTES = 8192;
constexpr int XBUF_OFF = NSLOT_O * SLOT_BYTES;
constexpr int BAR_OFF = NSLOT * SLOT_BYTES;
constexpr int FULLO = 192, EMPTYE = 360;
constexpr int SINK_OFF = BAR_OFF + 1024;
constexpr int PF_DEPTH = 9;
constexpr int SMEM_BYTES = SINK_OFF + PF_DEPTH * 960 + 1024;
constexpr int NTHREADS = 512;

struct Params {
  CUtensorMap x[2], wq[2], k[2], v[2], wo[2];
  const char* kp[2]; const char* vp[2]; const char* wqp[2]; const char* xp[2];
  unsigned int* epoch;
};

__device__ uint4 g_part[8 * 10 * 7 * (SLOT_BYTES / 16)];
__device__ unsigned int g_epoch[8];
#define TSTAMP(i)
#define PSTAMP(i)
#define HSTAMP(i)
#define GSTAMP(a, b)
#define HSTAMP2(i)
#define CSTAMP(i)
#define TDUMP()

#define XSTAMP(i)
#define ESTAMP(i) TSTAMP(i)
#define QSTAMP(i)
#define FSTAMP(i)
#define SNOW(v)
#define SPUT(i, v)
__device__ __forceinline__ uint32_t smem_u32(const void* p) { return (uint32_t)__cvta_generic_to_shared(p); }
__device__ __forceinline__ void mbar_init(uint32_t bar, uint32_t cnt) {
  asm volatile("mbarrier.init.shared::cta.b64 [%0], %1;" ::"r"(bar), "r"(cnt) : "memory");
}
__device__ __forceinline__ void mbar_expect_tx(uint32_t bar, uint32_t bytes) {
  asm volatile("mbarrier.arrive.expect_tx.shared::cta.b64 _, [%0], %1;" ::"r"(bar), "r"(bytes) : "memory");
}
__device__ __forceinline__ uint32_t mapa(uint32_t addr, uint32_t cta) {
  uint32_t r;
  asm volatile("mapa.shared::cluster.u32 %0, %1, %2;" : "=r"(r) : "r"(addr), "r"(cta));
  return r;
}
__device__ __forceinline__ void mbar_arrive_cluster(uint32_t remote_bar) {
  asm volatile("mbarrier.arrive.shared::cluster.b64 _, [%0];" ::"r"(remote_bar) : "memory");
}
__device__ __forceinline__ uint32_t mbar_try(uint32_t bar, uint32_t parity) {
  uint32_t ok;
  asm volatile("{\n.reg .pred p;\nmbarrier.try_wait.parity.shared::cta.b64 p, [%1], %2;\nselp.u32 %0, 1, 0, p;\n}\n"
               : "=r"(ok) : "r"(bar), "r"(parity) : "memory");
  return ok;
}
__device__ __forceinline__ uint32_t mbar_test(uint32_t bar, uint32_t parity) {
  uint32_t ok;
  asm volatile("{\n.reg .pred p;\nmbarrier.test_wait.parity.shared::cta.b64 p, [%1], %2;\nselp.u32 %0, 1, 0, p;\n}\n"
               : "=r"(ok) : "r"(bar), "r"(parity) : "memory");
  return ok;
}
__device__ __forceinline__ uint32_t mbar_try_cluster(uint32_t bar, uint32_t parity) {
  uint32_t ok;
  asm volatile("{\n.reg .pred p;\nmbarrier.try_wait.parity.acquire.cluster.shared::cta.b64 p, [%1], %2;\nselp.u32 %0, 1, 0, p;\n}\n"
               : "=r"(ok) : "r"(bar), "r"(parity) : "memory");
  return ok;
}
__device__ __forceinline__ uint32_t clk32() {
  uint32_t t;
  asm volatile("mov.u32 %0, %%clock;" : "=r"(t));
  return t;
}
#define DBGREC(a, b)
__device__ __forceinline__ void mbar_wait(uint32_t bar, uint32_t parity) {
  if (mbar_try(bar, parity)) return;
  const uint32_t t0 = clk32();
  while (!mbar_try(bar, parity)) {
    if (clk32() - t0 > SPIN_LIMIT) { DBGREC(bar, parity); break; }
  }
}
__device__ __forceinline__ void mbar_wait_cluster(uint32_t bar, uint32_t parity) {
  if (mbar_try_cluster(bar, parity)) return;
  const uint32_t t0 = clk32();
  while (!mbar_try_cluster(bar, parity)) {
    if (clk32() - t0 > SPIN_LIMIT) break;
  }
}
__device__ __forceinline__ void cluster_sync() {
  asm volatile("barrier.cluster.arrive.release.aligned;\nbarrier.cluster.wait.acquire.aligned;\n" ::: "memory");
}
__device__ __forceinline__ void tma2d(uint32_t dst, const CUtensorMap* m, int c0, int c1, uint32_t bar) {
  asm volatile("cp.async.bulk.tensor.2d.shared::cluster.global.mbarrier::complete_tx::bytes [%0], [%1, {%3, %4}], [%2];"
               ::"r"(dst), "l"(m), "r"(bar), "r"(c0), "r"(c1) : "memory");
}
__device__ __forceinline__ void tma2d_mc(uint32_t dst, const CUtensorMap* m, int c0, int c1, uint32_t bar, uint16_t mask) {
  asm volatile("cp.async.bulk.tensor.2d.shared::cluster.global.mbarrier::complete_tx::bytes.multicast::cluster [%0], [%1, {%3, %4}], [%2], %5;"
               ::"r"(dst), "l"(m), "r"(bar), "r"(c0), "r"(c1), "h"(mask) : "memory");
}
__device__ __forceinline__ void tma3d(uint32_t dst, const CUtensorMap* m, int c0, int c1, int c2, uint32_t bar) {
  asm volatile("cp.async.bulk.tensor.3d.shared::cluster.global.mbarrier::complete_tx::bytes [%0], [%1, {%3, %4, %5}], [%2];"
               ::"r"(dst), "l"(m), "r"(bar), "r"(c0), "r"(c1), "r"(c2) : "memory");
}
__device__ __forceinline__ void tma4d(uint32_t dst, const CUtensorMap* m, int c0, int c1, int c2, int c3, uint32_t bar) {
  asm volatile("cp.async.bulk.tensor.4d.shared::cluster.global.mbarrier::complete_tx::bytes [%0], [%1, {%3, %4, %5, %6}], [%2];"
               ::"r"(dst), "l"(m), "r"(bar), "r"(c0), "r"(c1), "r"(c2), "r"(c3) : "memory");
}
__device__ __forceinline__ void mbar_arrive(uint32_t bar) {
  asm volatile("mbarrier.arrive.shared::cta.b64 _, [%0];" ::"r"(bar) : "memory");
}
__device__ __forceinline__ uint32_t touch_l2(const void* p) {
  uint32_t v;
  asm volatile("ld.global.cg.L2::128B.b32 %0, [%1];" : "=r"(v) : "l"(p));
  return v;
}
__device__ __forceinline__ unsigned ld_acquire(const unsigned* p) {
  unsigned v;
  asm volatile("ld.acquire.gpu.global.u32 %0, [%1];" : "=r"(v) : "l"(p) : "memory");
  return v;
}
__device__ __forceinline__ void wg_fence() { asm volatile("wgmma.fence.sync.aligned;" ::: "memory"); }
__device__ __forceinline__ void wg_commit() { asm volatile("wgmma.commit_group.sync.aligned;" ::: "memory"); }
template <int N> __device__ __forceinline__ void wg_wait() { asm volatile("wgmma.wait_group.sync.aligned %0;" ::"n"(N) : "memory"); }
template <int N> __device__ __forceinline__ void fence_regs(float (&d)[N]) {
#pragma unroll
  for (int i = 0; i < N; i++) asm volatile("" : "+f"(d[i])::"memory");
}
template <int N> __device__ __forceinline__ void fence_regs(uint32_t (&d)[N]) {
#pragma unroll
  for (int i = 0; i < N; i++) asm volatile("" : "+r"(d[i])::"memory");
}
template <int N> __device__ __forceinline__ void pin_regs(const uint32_t* d, uint32_t never, uint32_t addr) {
#pragma unroll
  for (int i = 0; i < N; i += 4)
    asm volatile("{\n.reg .pred p;\nsetp.ne.u32 p, %5, 0;\n@p st.shared.v4.b32 [%0], {%1, %2, %3, %4};\n}\n"
                 ::"r"(addr), "r"(d[i]), "r"(d[i + 1]), "r"(d[i + 2]), "r"(d[i + 3]), "r"(never) : "memory");
}
__device__ __forceinline__ uint32_t pack_bf16(float lo, float hi) {
  uint32_t r;
  asm("cvt.rn.bf16x2.f32 %0, %1, %2;" : "=r"(r) : "f"(hi), "f"(lo));
  return r;
}
__device__ __forceinline__ float ex2(float x) {
  float r;
  asm("ex2.approx.ftz.f32 %0, %1;" : "=f"(r) : "f"(x));
  return r;
}
__device__ __forceinline__ float rcp(float x) {
  float r;
  asm("rcp.approx.ftz.f32 %0, %1;" : "=f"(r) : "f"(x));
  return r;
}
__device__ __forceinline__ uint64_t make_desc(uint32_t addr, uint32_t lbo, uint32_t sbo) {
  return (uint64_t)((addr & 0x3FFFFu) >> 4) | ((uint64_t)(lbo >> 4) << 16) | ((uint64_t)(sbo >> 4) << 32) | (1ull << 62);
}

__device__ __forceinline__ void wgmma_n192_ss_tb(float (&d)[96], uint64_t da, uint64_t db, int scale_d) {
  asm volatile("{\n.reg .pred p;\nsetp.ne.b32 p, %98, 0;\n"
    "wgmma.mma_async.sync.aligned.m64n192k16.f32.bf16.bf16 "
    "{%0, %1, %2, %3, %4, %5, %6, %7, %8, %9, %10, %11, %12, %13, %14, %15, %16, %17, %18, %19, %20, %21, %22, %23, %24, %25, %26, %27, %28, %29, %30, %31, %32, %33, %34, %35, %36, %37, %38, %39, %40, %41, %42, %43, %44, %45, %46, %47, %48, %49, %50, %51, %52, %53, %54, %55, %56, %57, %58, %59, %60, %61, %62, %63, %64, %65, %66, %67, %68, %69, %70, %71, %72, %73, %74, %75, %76, %77, %78, %79, %80, %81, %82, %83, %84, %85, %86, %87, %88, %89, %90, %91, %92, %93, %94, %95}, "
    "%96, %97, p, 1, 1, 0, 1;\n}\n"
    : "+f"(d[0]), "+f"(d[1]), "+f"(d[2]), "+f"(d[3]), "+f"(d[4]), "+f"(d[5]), "+f"(d[6]), "+f"(d[7]), "+f"(d[8]), "+f"(d[9]), "+f"(d[10]), "+f"(d[11]), "+f"(d[12]), "+f"(d[13]), "+f"(d[14]), "+f"(d[15]), "+f"(d[16]), "+f"(d[17]), "+f"(d[18]), "+f"(d[19]), "+f"(d[20]), "+f"(d[21]), "+f"(d[22]), "+f"(d[23]), "+f"(d[24]), "+f"(d[25]), "+f"(d[26]), "+f"(d[27]), "+f"(d[28]), "+f"(d[29]), "+f"(d[30]), "+f"(d[31]), "+f"(d[32]), "+f"(d[33]), "+f"(d[34]), "+f"(d[35]), "+f"(d[36]), "+f"(d[37]), "+f"(d[38]), "+f"(d[39]), "+f"(d[40]), "+f"(d[41]), "+f"(d[42]), "+f"(d[43]), "+f"(d[44]), "+f"(d[45]), "+f"(d[46]), "+f"(d[47]), "+f"(d[48]), "+f"(d[49]), "+f"(d[50]), "+f"(d[51]), "+f"(d[52]), "+f"(d[53]), "+f"(d[54]), "+f"(d[55]), "+f"(d[56]), "+f"(d[57]), "+f"(d[58]), "+f"(d[59]), "+f"(d[60]), "+f"(d[61]), "+f"(d[62]), "+f"(d[63]), "+f"(d[64]), "+f"(d[65]), "+f"(d[66]), "+f"(d[67]), "+f"(d[68]), "+f"(d[69]), "+f"(d[70]), "+f"(d[71]), "+f"(d[72]), "+f"(d[73]), "+f"(d[74]), "+f"(d[75]), "+f"(d[76]), "+f"(d[77]), "+f"(d[78]), "+f"(d[79]), "+f"(d[80]), "+f"(d[81]), "+f"(d[82]), "+f"(d[83]), "+f"(d[84]), "+f"(d[85]), "+f"(d[86]), "+f"(d[87]), "+f"(d[88]), "+f"(d[89]), "+f"(d[90]), "+f"(d[91]), "+f"(d[92]), "+f"(d[93]), "+f"(d[94]), "+f"(d[95])
    : "l"(da), "l"(db), "r"(scale_d));
}
__device__ __forceinline__ void wgmma_n96_rs(float (&d)[48], uint32_t a0, uint32_t a1, uint32_t a2, uint32_t a3, uint64_t db, int scale_d) {
  asm volatile("{\n.reg .pred p;\nsetp.ne.b32 p, %53, 0;\n"
    "wgmma.mma_async.sync.aligned.m64n96k16.f32.bf16.bf16 "
    "{%0, %1, %2, %3, %4, %5, %6, %7, %8, %9, %10, %11, %12, %13, %14, %15, %16, %17, %18, %19, %20, %21, %22, %23, %24, %25, %26, %27, %28, %29, %30, %31, %32, %33, %34, %35, %36, %37, %38, %39, %40, %41, %42, %43, %44, %45, %46, %47}, "
    "{%48, %49, %50, %51}, %52, p, 1, 1, 0;\n}\n"
    : "+f"(d[0]), "+f"(d[1]), "+f"(d[2]), "+f"(d[3]), "+f"(d[4]), "+f"(d[5]), "+f"(d[6]), "+f"(d[7]), "+f"(d[8]), "+f"(d[9]), "+f"(d[10]), "+f"(d[11]), "+f"(d[12]), "+f"(d[13]), "+f"(d[14]), "+f"(d[15]), "+f"(d[16]), "+f"(d[17]), "+f"(d[18]), "+f"(d[19]), "+f"(d[20]), "+f"(d[21]), "+f"(d[22]), "+f"(d[23]), "+f"(d[24]), "+f"(d[25]), "+f"(d[26]), "+f"(d[27]), "+f"(d[28]), "+f"(d[29]), "+f"(d[30]), "+f"(d[31]), "+f"(d[32]), "+f"(d[33]), "+f"(d[34]), "+f"(d[35]), "+f"(d[36]), "+f"(d[37]), "+f"(d[38]), "+f"(d[39]), "+f"(d[40]), "+f"(d[41]), "+f"(d[42]), "+f"(d[43]), "+f"(d[44]), "+f"(d[45]), "+f"(d[46]), "+f"(d[47])
    : "r"(a0), "r"(a1), "r"(a2), "r"(a3), "l"(db), "r"(scale_d));
}
__device__ __forceinline__ void wgmma_n64_rs_tb(float (&d)[32], uint32_t a0, uint32_t a1, uint32_t a2, uint32_t a3, uint64_t db, int scale_d) {
  asm volatile("{\n.reg .pred p;\nsetp.ne.b32 p, %37, 0;\n"
    "wgmma.mma_async.sync.aligned.m64n64k16.f32.bf16.bf16 "
    "{%0, %1, %2, %3, %4, %5, %6, %7, %8, %9, %10, %11, %12, %13, %14, %15, %16, %17, %18, %19, %20, %21, %22, %23, %24, %25, %26, %27, %28, %29, %30, %31}, "
    "{%32, %33, %34, %35}, %36, p, 1, 1, 1;\n}\n"
    : "+f"(d[0]), "+f"(d[1]), "+f"(d[2]), "+f"(d[3]), "+f"(d[4]), "+f"(d[5]), "+f"(d[6]), "+f"(d[7]), "+f"(d[8]), "+f"(d[9]), "+f"(d[10]), "+f"(d[11]), "+f"(d[12]), "+f"(d[13]), "+f"(d[14]), "+f"(d[15]), "+f"(d[16]), "+f"(d[17]), "+f"(d[18]), "+f"(d[19]), "+f"(d[20]), "+f"(d[21]), "+f"(d[22]), "+f"(d[23]), "+f"(d[24]), "+f"(d[25]), "+f"(d[26]), "+f"(d[27]), "+f"(d[28]), "+f"(d[29]), "+f"(d[30]), "+f"(d[31])
    : "r"(a0), "r"(a1), "r"(a2), "r"(a3), "l"(db), "r"(scale_d));
}

__device__ __forceinline__ int chunk_of(int i, int off) { const int c = i + off; return c >= 10 ? c - 10 : c; }
__device__ __forceinline__ int pos_of(int i, int c) { return i - (i > chunk_of(c, 6)) - (i > chunk_of(c, 1)); }
__device__ __forceinline__ int index_at(int t, int r, bool fin) { return (r == 0 && (t < 8 || fin)) ? (t ^ 1) : t; }

constexpr int KPOS = 43;
__device__ __forceinline__ void do_item(const Params& P, int i, int p, int tg, int h0, int r, uint32_t dst, uint32_t bar) {
  if (i >= 46) {
    const int h1 = i >= 49;
    tma4d(dst, &P.v[p], (i - 46 - 3 * h1) * 64, 0, h0 + HS * h1, tg * 4, bar);
  } else if (i >= KPOS && i < KPOS + 3) {
    tma4d(dst, &P.k[p], (i - KPOS) * 64, 0, h0 + HS, tg * 4, bar);
  } else if (i >= 20 && i < 23) {
    tma4d(dst, &P.k[p], (i - 20) * 64, 0, h0, tg * 4, bar);
  } else {
    const int hh = i >= 23;
    const int j = i - 23 * hh - 3 * (i >= KPOS);
    const int kc = j >> 1;
    if (!(j & 1)) tma2d_mc(dst + r * 12288, &P.x[p], kc * 64, tg * 192 + r * 96, bar, (uint16_t)3);
    else tma3d(dst, &P.wq[p], 0, kc * 64, (h0 + HS * hh) * 3, bar);
  }
}

struct Ring {
  uint32_t slot, phase;
  __device__ __forceinline__ void advance() {
    if (++slot == NSLOT) { slot = 0; phase ^= 1; }
  }
};

__device__ __forceinline__ void load_tile(uint32_t (&x)[16], uint32_t addr) {
#pragma unroll
  for (int j = 0; j < 4; j++)
    asm volatile("ld.shared.v4.b32 {%0, %1, %2, %3}, [%4];"
                 : "=r"(x[4 * j]), "=r"(x[4 * j + 1]), "=r"(x[4 * j + 2]), "=r"(x[4 * j + 3]) : "r"(addr + j * 2048) : "memory");
}
__device__ __forceinline__ void store_tile(uint32_t addr, const float (&a)[32]) {
#pragma unroll
  for (int j = 0; j < 4; j++)
    asm volatile("st.shared.v4.b32 [%0], {%1, %2, %3, %4};"
                 ::"r"(addr + j * 2048), "r"(pack_bf16(a[8 * j], a[8 * j + 1])), "r"(pack_bf16(a[8 * j + 2], a[8 * j + 3])),
                   "r"(pack_bf16(a[8 * j + 4], a[8 * j + 5])), "r"(pack_bf16(a[8 * j + 6], a[8 * j + 7])) : "memory");
}
__device__ __forceinline__ uint32_t add_bf16x2(uint32_t a, uint32_t b) {
  uint32_t r;
  asm("add.rn.bf16x2 %0, %1, %2;" : "=r"(r) : "r"(a), "r"(b));
  return r;
}
template <int LUT> __device__ __forceinline__ uint32_t lop3(uint32_t a, uint32_t b, uint32_t c) {
  uint32_t r;
  asm("lop3.b32 %0, %1, %2, %3, %4;" : "=r"(r) : "r"(a), "r"(b), "r"(c), "n"(LUT));
  return r;
}
__device__ __forceinline__ uint32_t tile_ok(const uint32_t (&y)[16], uint32_t tm) {
  return (y[0] ^ tm) & (y[4] ^ tm) & (y[8] ^ tm) & (y[12] ^ tm) & 1u;
}
__device__ __forceinline__ void add_tile(float (&a)[32], const uint32_t (&x)[16]) {
#pragma unroll
  for (int j = 0; j < 16; j++) {
    a[2 * j] += __uint_as_float(x[j] << 16);
    a[2 * j + 1] += __uint_as_float(x[j] & 0xffff0000u);
  }
}
__device__ __forceinline__ uint32_t ophys(uint32_t s) { return (0x26057431u >> (4 * s)) & 7u; }

struct Front {
  Ring rg;
  uint32_t sbase, full0, rel0, never;
  int w, lane, hf;
  __device__ __forceinline__ uint32_t tsb() const { return full0 + 512 + w * 128; }
  __device__ __forceinline__ void release(uint32_t s) const { if (lane < 2) mbar_arrive_cluster(rel0 + 8 * s); }
  __device__ __forceinline__ uint32_t next() {
    const uint32_t s = rg.slot;
    mbar_wait(full0 + 8 * s, rg.phase);
    rg.advance();
    return s;
  }
  template <bool FIRST> __device__ __forceinline__ void qchunk(float (&acc)[96], uint32_t& sx, uint32_t& sw) {
    sx = next(); sw = next();
    const uint64_t da = make_desc(sbase + sx * SLOT_BYTES + w * 8192, 16, 1024);
    const uint64_t db = make_desc(sbase + sw * SLOT_BYTES, 8192, 1024);
    wg_fence();
#pragma unroll
    for (int s = 0; s < QMMA; s++) wgmma_n192_ss_tb(acc, da + 2 * s, db + 128 * s, !FIRST || s != 0);
    wg_commit();
  }
  __device__ __forceinline__ void qrest(float (&acc)[96], uint32_t (&qf)[48], uint32_t psx, uint32_t psw, int kc0, int tbase) {
#pragma unroll 1
    for (int kc = kc0; kc < 10; kc++) {
      uint32_t sx, sw;
      qchunk<false>(acc, sx, sw);
      QSTAMP(20 + kc);
      wg_wait<1>(); release(psx); release(psw);
      psx = sx; psw = sw;
    }
    wg_wait<0>();
    fence_regs(acc);
    release(psx); release(psw);
#pragma unroll
    for (int i = 24; i < 48; i++) qf[i] = pack_bf16(acc[2 * i], acc[2 * i + 1]);
    pin_regs<24>(qf + 24, never, full0);
#pragma unroll
    for (int i = 0; i < 24; i++) qf[i] = pack_bf16(acc[2 * i], acc[2 * i + 1]);
    pin_regs<24>(qf, never, full0);
    fence_regs(qf);
  }
  __device__ __forceinline__ void scores(float (&v)[24], const uint32_t (&qf)[48]) {
    float sacc[48];
    uint32_t ks[3];
#pragma unroll
    for (int dc = 0; dc < 3; dc++) {
      ks[dc] = next();
      const uint64_t db = make_desc(sbase + ks[dc] * SLOT_BYTES + w * 6144, 16, 1024);
      wg_fence();
#pragma unroll
      for (int s = 0; s < 4; s++) {
        const int j = dc * 4 + s;
        wgmma_n96_rs(sacc, qf[4 * j], qf[4 * j + 1], qf[4 * j + 2], qf[4 * j + 3], db + 2 * s, j != 0);
      }
    }
    wg_commit();
    wg_wait<0>();
    fence_regs(sacc);
    release(ks[0]); release(ks[1]); release(ks[2]);
#pragma unroll
    for (int i = 0; i < 24; i++) v[i] = hf ? sacc[24 + i] : sacc[i];
    fence_regs(v);
  }
  __device__ __forceinline__ void softmax(uint32_t (&pk)[12], float (&v)[24]) {
    float m0 = v[0], m1 = v[2];
#pragma unroll
    for (int t = 0; t < 6; t++) {
      m0 = fmaxf(m0, fmaxf(v[4 * t], v[4 * t + 1]));
      m1 = fmaxf(m1, fmaxf(v[4 * t + 2], v[4 * t + 3]));
    }
    m0 = fmaxf(m0, __shfl_xor_sync(0xffffffffu, m0, 1));
    m1 = fmaxf(m1, __shfl_xor_sync(0xffffffffu, m1, 1));
    m0 = fmaxf(m0, __shfl_xor_sync(0xffffffffu, m0, 2));
    m1 = fmaxf(m1, __shfl_xor_sync(0xffffffffu, m1, 2));
    const float cs = 0.07216878364870322f * 1.4426950408889634f;
    const float b0 = m0 * cs, b1 = m1 * cs;
    float s0 = 0.f, s1 = 0.f;
#pragma unroll
    for (int t = 0; t < 6; t++) {
      v[4 * t] = ex2(fmaf(v[4 * t], cs, -b0));
      v[4 * t + 1] = ex2(fmaf(v[4 * t + 1], cs, -b0));
      v[4 * t + 2] = ex2(fmaf(v[4 * t + 2], cs, -b1));
      v[4 * t + 3] = ex2(fmaf(v[4 * t + 3], cs, -b1));
      s0 += v[4 * t] + v[4 * t + 1];
      s1 += v[4 * t + 2] + v[4 * t + 3];
    }
    s0 += __shfl_xor_sync(0xffffffffu, s0, 1);
    s1 += __shfl_xor_sync(0xffffffffu, s1, 1);
    s0 += __shfl_xor_sync(0xffffffffu, s0, 2);
    s1 += __shfl_xor_sync(0xffffffffu, s1, 2);
    const float r0 = rcp(s0), r1 = rcp(s1);
#pragma unroll
    for (int t = 0; t < 6; t++) {
      pk[2 * t] = pack_bf16(v[4 * t] * r0, v[4 * t + 1] * r0);
      pk[2 * t + 1] = pack_bf16(v[4 * t + 2] * r1, v[4 * t + 3] * r1);
    }
    pin_regs<12>(pk, never, full0);
    fence_regs(pk);
  }
  __device__ __forceinline__ void expand(uint32_t (&pa)[24], uint32_t (&pk)[12]) {
    fence_regs(pk);
#pragma unroll
    for (int i = 0; i < 12; i++) {
      pa[i] = hf ? 0u : pk[i];
      pa[12 + i] = hf ? pk[i] : 0u;
    }
    fence_regs(pa);
  }
  __device__ __forceinline__ void pv(float (&oa)[32], const uint32_t (&pa)[24], int s, int parity) {
    mbar_wait(full0 + 8 * s, parity);
    const uint64_t db = make_desc(sbase + s * SLOT_BYTES + w * 6144, 16, 1024);
    wg_fence();
#pragma unroll
    for (int j = 0; j < 6; j++) wgmma_n64_rs_tb(oa, pa[4 * j], pa[4 * j + 1], pa[4 * j + 2], pa[4 * j + 3], db + 128 * j, j != 0);
  }
  __device__ __forceinline__ void pack16(uint32_t* o, const float (&oa)[32]) {
#pragma unroll
    for (int i = 0; i < 16; i++) o[i] = pack_bf16(oa[2 * i], oa[2 * i + 1]);
    pin_regs<16>(o, never, full0);
  }
  __device__ __forceinline__ void early(float (&a)[32], const uint32_t (&o0)[48], int t) {
    mbar_wait(full0 + FULLO + 16 * t, 0);
    const uint64_t db = make_desc(sbase + (4 + t) * SLOT_BYTES, 16, 1024);
    wg_fence();
#pragma unroll
    for (int j = 0; j < 12; j++)
      wgmma_n64_rs_tb(a, o0[4 * j], o0[4 * j + 1], o0[4 * j + 2], o0[4 * j + 3], db + 128 * j, j != 0);
    wg_commit();
  }
  __device__ __forceinline__ void park(float (&a)[32], int t) {
    fence_regs(a);
    if (lane == 0) mbar_arrive(full0 + EMPTYE + 8 * (t + 1));
    mbar_wait(full0 + EMPTYE + 8 * t, 0);
    uint32_t tid;
    asm volatile("mov.u32 %0, %%tid.x;" : "=r"(tid));
    store_tile(sbase + ophys(2 * t) * SLOT_BYTES + (tid >> 7) * XBUF_BYTES + (tid & 127) * 16, a);
  }
  __device__ __forceinline__ void run(uint32_t (&o0)[48], uint32_t (&o1)[48]) {
    uint32_t pk[12], pa[24];
    float v[24];
    {
      uint32_t qf[48];
      {
        float acc[96];
        uint32_t sx, sw;
        qchunk<true>(acc, sx, sw);
        { const int tbase = 1; (void)tbase; QSTAMP(20); }
        qrest(acc, qf, sx, sw, 1, 1);
      }
      TSTAMP(1);
      scores(v, qf);
      TSTAMP(2);
    }
    {
      uint32_t qf[48];
      {
        float acc[96];
        uint32_t ax, aw, bx, bw;
        qchunk<true>(acc, ax, aw);
        qchunk<false>(acc, bx, bw);
        softmax(pk, v);
        TSTAMP(3);
        wg_wait<1>(); release(ax); release(aw);
        qrest(acc, qf, bx, bw, 2, 4);
      }
      TSTAMP(4);
      scores(v, qf);
      TSTAMP(5);
    }
    {
      float oa[32], ob[32], oc[32];
      expand(pa, pk);
      pv(oa, pa, 1, 1); pv(ob, pa, 2, 1); pv(oc, pa, 3, 1);
      wg_commit();
      XSTAMP(20);
      softmax(pk, v);
      XSTAMP(21);
      wg_wait<0>();
      fence_regs(oa); fence_regs(ob); fence_regs(oc);
      XSTAMP(22);
      release(2); release(3);
      if (lane == 0) mbar_arrive(full0 + EMPTYE);
      pack16(o0, oa); pack16(o0 + 16, ob); pack16(o0 + 32, oc);
      fence_regs(o0);
    }
    {
      float oa[32], ob[32];
      early(oa, o0, 0);
      early(ob, o0, 1);
      XSTAMP(23);
      wg_wait<1>(); park(oa, 0);
      early(oa, o0, 2);
      wg_wait<1>(); park(ob, 1);
      early(ob, o0, 3);
      XSTAMP(24);
      wg_wait<1>(); park(oa, 2);
      wg_wait<0>(); park(ob, 3);
      XSTAMP(25);
      fence_regs(o0);
#pragma unroll
      for (int i = 0; i < 12; i++) o0[i] += never;
      fence_regs(o0);
      expand(pa, pk);
      pv(oa, pa, 8, 1);
      pv(ob, pa, 0, 0);
      wg_commit();
      XSTAMP(26);
      wg_wait<0>();
      fence_regs(oa); fence_regs(ob);
      XSTAMP(27);
      release(8); release(0);
      pack16(o1, oa); pack16(o1 + 16, ob);
      float oc[32];
      pv(oc, pa, 2, 0);
      wg_commit();
      XSTAMP(28);
      wg_wait<0>();
      fence_regs(oc);
      release(2);
      pack16(o1 + 32, oc);
    }
    TSTAMP(6);
  }
};

__device__ __forceinline__ uint32_t oslot_addr(uint32_t sbase, uint32_t s) { return sbase + ophys(s) * SLOT_BYTES; }
template <bool EARLY>
__device__ __forceinline__ void oproj_chunk(float (&a)[32], const uint32_t (&o0)[48], const uint32_t (&o1)[48], int t, uint32_t toff,
                                            uint32_t sbase, uint32_t fullo0, uint32_t emptyo0, int lane, int w, int wnext, bool pass) {
  const uint32_t s0 = (2 * t) & 7, s1 = s0 + 1, ph = (t >> 2) & 1;
  if (EARLY) {
    uint32_t x[16];
    load_tile(x, oslot_addr(sbase, s0) + toff);
#pragma unroll
    for (int j = 0; j < 16; j++) {
      a[2 * j] = __uint_as_float(x[j] << 16);
      a[2 * j + 1] = __uint_as_float(x[j] & 0xffff0000u);
    }
    fence_regs(a);
    if (!(t & 1)) {
      __syncwarp();
      if (lane == 0) mbar_arrive(emptyo0 + 8 * s0);
    }
  } else {
    mbar_wait(fullo0 + 8 * s0, ph);
  }
  mbar_wait(fullo0 + 8 * s1, ph);
  asm volatile("bar.sync %0, 256;" ::"r"(1 + w) : "memory");
  wg_fence();
  if (!EARLY) {
    const uint64_t db = make_desc(oslot_addr(sbase, s0), 16, 1024);
#pragma unroll
    for (int j = 0; j < 12; j++)
      wgmma_n64_rs_tb(a, o0[4 * j], o0[4 * j + 1], o0[4 * j + 2], o0[4 * j + 3], db + 128 * j, j != 0);
    wg_commit();
  }
  {
    const uint64_t db = make_desc(oslot_addr(sbase, s1), 16, 1024);
#pragma unroll
    for (int j = 0; j < 12; j++) {
      wgmma_n64_rs_tb(a, o1[4 * j], o1[4 * j + 1], o1[4 * j + 2], o1[4 * j + 3], db + 128 * j, 1);
      if (j == TOKEN_AT && pass) asm volatile("bar.arrive %0, 256;" ::"r"(1 + wnext) : "memory");
    }
    wg_commit();
  }
  if (!EARLY) {
    wg_wait<1>();
    if (lane == 0) mbar_arrive(emptyo0 + 8 * s0);
  }
  wg_wait<0>();
  fence_regs(a);
  if (lane == 0) mbar_arrive(emptyo0 + 8 * s1);
}

__global__ void __cluster_dims__(2, 1, 1) __launch_bounds__(NTHREADS, 1)
fused_kernel(const __grid_constant__ Params P, __nv_bfloat16* __restrict__ out) {
  extern __shared__ uint8_t smem_raw[];
  const uint32_t sbase = (smem_u32(smem_raw) + 1023u) & ~1023u;
  const uint32_t full0 = sbase + BAR_OFF;
  const uint32_t empty0 = full0 + 72;
  const uint32_t xfull0 = full0 + 144;
  const uint32_t xempty0 = full0 + 168;
  const uint32_t fullo0 = full0 + FULLO;
  const uint32_t emptyo0 = full0 + 256;
  const uint32_t ready0 = full0 + 400;
  const uint32_t eready = full0 + 344;
  const uint32_t epoch_s = full0 + 352;
  const uint32_t emptye0 = full0 + EMPTYE;

  const int tid = threadIdx.x, lane = tid & 31;
  const int warp = __shfl_sync(0xffffffffu, tid >> 5, 0);
  auto tsb = [&]() { return full0 + 512 + (warp >> 2) * 128; };
  const int bid = blockIdx.x;
  const int hp = bid & 15, tg = (bid >> 4) & 3, p = bid >> 6;
  const int r = hp & 1;
  const int h0 = hp * HM;
  const int grp = p * 4 + tg;
  const int off = (hp >> 1) + (hp >> 3);
  const bool fin = r == 1 || off == 0 || off == 5;

  if (warp >= 12) {
    asm volatile("setmaxnreg.dec.sync.aligned.u32 32;");
    if (tid == 384) {
#pragma unroll
      for (int i = 2; i < NSLOT; i++) mbar_init(full0 + 8 * i, 1);
      asm volatile("fence.mbarrier_init.release.cluster;" ::: "memory");
    }
    __syncwarp();
    asm volatile("barrier.cluster.arrive.relaxed.aligned;" ::: "memory");
    if (warp == 12) {
      SNOW(sa_);
      if (lane == 0) {
#pragma unroll 1
        for (int c = 1; c < 5; c++) {
          if (c == FDELAY_C) { const uint32_t t0 = clk32(); while (clk32() - t0 < FDELAY) {} }
          mbar_expect_tx(full0 + 16 * c, SLOT_BYTES);
          tma2d(sbase + 2 * c * SLOT_BYTES, &P.x[p], c * 64, tg * 192, full0 + 16 * c);
          tma2d(sbase + 2 * c * SLOT_BYTES + 12288, &P.x[p], c * 64, tg * 192 + 96, full0 + 16 * c);
          if (c == 4) break;
          mbar_expect_tx(full0 + 8 + 16 * c, SLOT_BYTES);
          tma3d(sbase + (2 * c + 1) * SLOT_BYTES, &P.wq[p], 0, c * 64, h0 * 3, full0 + 8 + 16 * c);
        }
        asm volatile("prefetch.tensormap [%0];" ::"l"(&P.k[p]) : "memory");
        asm volatile("prefetch.tensormap [%0];" ::"l"(&P.v[p]) : "memory");
        asm volatile("prefetch.tensormap [%0];" ::"l"(&P.wo[p]) : "memory");
      }
      SNOW(sb_);
      __syncwarp();
      asm volatile("barrier.cluster.wait.aligned;" ::: "memory");
      if (lane == 0) {
        TSTAMP(3); CSTAMP(28);
        uint32_t slot = 0, phase = 1;
#pragma unroll 1
        for (int i = NSLOT; i < 49; i++) {
          mbar_wait(empty0 + 8 * slot, phase ^ 1);
          mbar_expect_tx(full0 + 8 * slot, SLOT_BYTES);
          do_item(P, i, p, tg, h0, r, sbase + slot * SLOT_BYTES, full0 + 8 * slot);
          if (++slot == NSLOT) { slot = 0; phase ^= 1; }
        }
        TSTAMP(2); CSTAMP(29);
#pragma unroll 1
        for (int e = 0; e < 23; e++) {
          int j = e - 3;
          if (e < 11) {
            slot = (uint32_t)(0x20732087654ull >> (4 * e)) & 15u;
            if (e == 8) mbar_wait(emptye0 + 32, 0);
            else mbar_wait(empty0 + 8 * slot, e >= 5 && e < 8);
            if (e >= 4 && e < 7) {
              mbar_expect_tx(full0 + 8 * slot, SLOT_BYTES);
              do_item(P, 45 + e, p, tg, h0, r, sbase + slot * SLOT_BYTES, full0 + 8 * slot);
              continue;
            }
            j = e < 4 ? 2 * e : 2 * e - 13;
          } else {
            slot = ophys(j & 7);
            mbar_wait(emptyo0 + 8 * (j & 7), ((j >> 3) & 1) ^ 1);
            if (j < 16) asm volatile("fence.proxy.async.shared::cta;" ::: "memory");
          }
          mbar_expect_tx(fullo0 + 8 * (j & 7), SLOT_BYTES);
          tma2d(sbase + slot * SLOT_BYTES, &P.wo[p], chunk_of(index_at(j >> 1, r, fin), off) * 64, (h0 + HS * (j & 1)) * 192, fullo0 + 8 * (j & 7));
        }
        TSTAMP(1); CSTAMP(30);
        if (fin) {
          const uint4* src = g_part + (size_t)(grp * 10 + chunk_of(8 + r, off)) * 7 * (SLOT_BYTES / 16);
#pragma unroll 1
          for (int g = 0; g < 4; g++) {
            mbar_wait(emptyo0 + 8 * (4 + g), 1);
            if (g == 0) mbar_expect_tx(fullo0 + 8 * 4, 4 * SLOT_BYTES);
            TSTAMP(4 + g);
            asm volatile("cp.async.bulk.shared::cluster.global.mbarrier::complete_tx::bytes [%0], [%1], %2, [%3];"
                         ::"r"(oslot_addr(sbase, 4 + g)), "l"(src + g * (SLOT_BYTES / 16)), "r"(SLOT_BYTES), "r"(fullo0 + 8 * 4) : "memory");
          }
        }
      }
    } else {
      const int w = warp - 13;
      unsigned epoch;
      asm volatile("ld.global.cg.u32 %0, [%1];" : "=r"(epoch) : "l"(P.epoch + grp));
      {
        uint32_t sink = sbase + SINK_OFF + (w * 20 + lane) * 16;
        int un = 0;
        uint32_t rot = 0;
        asm volatile("barrier.cluster.wait.aligned;" ::: "memory");
        mbar_wait(full0 + 8 * PF_TRIG, 0);
        uint32_t due = clk32();
#pragma unroll 1
        for (int ph = PF0 ? -1 : 0; ph < 5; ph++) {
          const char* q;
          int nb = 4, nt = 3, nl = 16;
          uint32_t sb = 589824;
          if (ph == 1 || ph < 0) {
            q = P.wqp[p] + (size_t)(lane * 4 + tg) * 12288 + (h0 + HS * (ph > 0)) * 384 + w * 128;
            nb = 10; nt = 1; sb = 786432;
            if (ph < 0) {
              nl = 20;
              if (lane >= 16) { q = P.xp[p] + (size_t)(tg * 192 + hp * 12 + w * 4 + lane - 16) * 1280; sb = 128; }
              nb = 10 - PF0_FROM; q += PF0_FROM * sb;
            }
          } else {
            q = (ph < 3 ? P.kp[p] : P.vp[p]) + (size_t)(tg * 128 + h0 + HS * (ph == 2 || ph == 4)) * 18432 + (w * 16 + lane) * 128;
          }
#pragma unroll 1
          for (int b = 0; b < nb; b++, q += sb) {
            if (ph > 0 && mbar_test(emptye0 + 32, 0)) break;
#pragma unroll 1
            for (int t = 0; t < nt; t++) {
              if (ph < 0) asm volatile("cp.async.wait_group %0;" ::"n"(PF_WIN0 - 1) : "memory");
              else if (ph < PF_NW) asm volatile("cp.async.wait_group %0;" ::"n"(PF_WIN1 - 1) : "memory");
              else asm volatile("cp.async.wait_group %0;" ::"n"(PF_WIN - 1) : "memory");
              if (PACE) {
                while ((int)(clk32() - due) < 0) __nanosleep(32);
                due += PACE;
              }
              if (!(un & 1)) { PSTAMP(un >> 1); }
              if (lane < nl)
                asm volatile("cp.async.cg.shared.global.L2::128B [%0], [%1], 16;" ::"r"(sink + rot), "l"(q + t * 6144) : "memory");
              asm volatile("cp.async.commit_group;" ::: "memory");
              un++;
              rot = rot == (PF_DEPTH - 1) * 960 ? 0 : rot + 960;
            }
          }
          if (ph == 0) {
            if (lane == 0) {
              asm volatile("st.shared.u32 [%0], %1;" ::"r"(epoch_s), "r"(epoch) : "memory");
              mbar_arrive(eready);
            }
          }
        }
        asm volatile("cp.async.wait_all;" ::: "memory");
      }
      if (lane == 0) {
#pragma unroll 1
        for (int k = 0; k < 4; k++) {
          const int c = chunk_of(2 * k + r, off), pos = pos_of(2 * k + r, c);
          uint4* dst = g_part + (size_t)((grp * 10 + c) * 7 + pos) * (SLOT_BYTES / 16) + w * 512;
          const uint32_t src = (k < 2 ? oslot_addr(sbase, 4 * k + 2) : sbase + XBUF_OFF) + w * XBUF_BYTES;
          mbar_wait(ready0 + 24 * k + 8 * w, 0);
          asm volatile("fence.proxy.async.shared::cta;" ::: "memory");
          asm volatile("cp.async.bulk.global.shared::cta.bulk_group [%0], [%1], %2;" ::"l"(dst), "r"(src), "r"(XBUF_BYTES) : "memory");
          asm volatile("cp.async.bulk.commit_group;" ::: "memory");
          asm volatile("cp.async.bulk.wait_group.read 0;" ::: "memory");
          if (k < 2) {
            asm volatile("mbarrier.arrive.shared::cta.b64 _, [%0], 4;" ::"r"(emptyo0 + 8 * (4 * k + 2)) : "memory");
          } else {
            mbar_expect_tx(xfull0 + 8 * w, XBUF_BYTES);
            asm volatile("mbarrier.arrive.shared::cluster.b64 _, [%0], 4;" ::"r"(mapa(xempty0 + 8 * w, r ^ 1)) : "memory");
          }
        }
      }
    }
    __syncwarp();
    TDUMP();
  } else {
    if (tid == 0) {
      asm volatile("prefetch.tensormap [%0];" ::"l"(&P.x[p]) : "memory");
      asm volatile("prefetch.tensormap [%0];" ::"l"(&P.wq[p]) : "memory");
    }
    {
      const int c = tid & 7, rr = tid >> 3;
      const uint32_t d = sbase + rr * 128 + ((c ^ (rr & 7)) << 4);
      const char* gw = P.wqp[p] + (size_t)(rr & 15) * 12288 + (h0 * 3 + (rr >> 4)) * 128 + c * 16;
      const uint32_t dw = sbase + SLOT_BYTES + (rr >> 4) * 8192 + (rr & 15) * 128 + ((c ^ (rr & 7)) << 4);
      const char* gx = P.xp[p] + (size_t)(tg * 192 + rr) * 1280 + c * 16;
#pragma unroll
      for (int i = 0; i < 4; i++) {
        asm volatile("cp.async.cg.shared.global [%0], [%1], 16;" ::"r"(dw + i * 2048), "l"(gw + i * 196608) : "memory");
        asm volatile("cp.async.cg.shared.global [%0], [%1], 16;" ::"r"(d + i * 6144), "l"(gx + i * 61440) : "memory");
      }
    }
    if (tid == 128) {
      mbar_init(full0, 1); mbar_init(full0 + 8, 1);
      for (int i = 0; i < NSLOT; i++) mbar_init(empty0 + 8 * i, 24);
      for (int i = 0; i < 3; i++) { mbar_init(xfull0 + 8 * i, 1); mbar_init(xempty0 + 8 * i, 4); }
      for (int i = 0; i < 12; i++) mbar_init(ready0 + 8 * i, 4);
      mbar_init(eready, 3);
      for (int i = 0; i < 5; i++) mbar_init(emptye0 + 8 * i, 12);
      for (int i = 0; i < NSLOT_O; i++) { mbar_init(fullo0 + 8 * i, 1); mbar_init(emptyo0 + 8 * i, 12); }
      asm volatile("fence.mbarrier_init.release.cluster;" ::: "memory");
      for (int i = 0; i < 3; i++) mbar_expect_tx(xfull0 + 8 * i, XBUF_BYTES);
      mbar_arrive(full0); mbar_arrive(full0 + 8);
    }
    __syncwarp();
    asm volatile("barrier.cluster.arrive.relaxed.aligned;" ::: "memory");
    asm volatile("setmaxnreg.inc.sync.aligned.u32 160;");
    SNOW(sd_);
    asm volatile("barrier.cluster.wait.aligned;" ::: "memory");
    asm volatile("cp.async.wait_all;" ::: "memory");
    asm volatile("fence.proxy.async.shared::cta;" ::: "memory");
    asm volatile("bar.sync 4, 384;" ::: "memory");
    const int w = warp >> 2;
    const int hf = warp / 3 - w;
    uint32_t o0[48], o1[48];
    const uint32_t never = (out == nullptr);
    {
      Front f{{0, 0}, sbase, full0, mapa(empty0, lane & 1), never, w, lane, hf};
      f.run(o0, o1);
    }
#pragma unroll
    for (int i = 0; i < 12; i++) o0[i] ^= never;
    fence_regs(o0); fence_regs(o1);

    const int wt = tid & 127;
    const int wnext = w == 2 ? 0 : w + 1;
    if (w == 2) asm volatile("bar.arrive 1, 256;" ::: "memory");
    const uint32_t xb = sbase + XBUF_OFF + w * XBUF_BYTES + wt * 16;
    mbar_wait(eready, 0);
    uint32_t tag;
    asm volatile("ld.shared.u32 %0, [%1];" : "=r"(tag) : "r"(epoch_s) : "memory");
    tag = __shfl_sync(0xffffffffu, ~tag & 1u, 0);
    float a[32];
    auto epilogue = [&](int t) {
      const int k = t >> 1;
      const int ci = index_at(t, r, fin);
      if ((ci & 1) != r) {
        if (k == 0) mbar_wait(empty0 + 8 * 8, 1);
        else mbar_wait(xempty0 + 8 * w, (k - 1) & 1);
        FSTAMP(20);
        const uint32_t rxb = mapa(xb, r ^ 1);
        const uint32_t rbar = mapa(xfull0 + 8 * w, r ^ 1);
#pragma unroll
        for (int j = 0; j < 4; j++)
          asm volatile("st.async.weak.shared::cluster.mbarrier::complete_tx::bytes.v4.b32 [%0], {%1, %2, %3, %4}, [%5];"
                       ::"r"(rxb + j * 2048), "r"(pack_bf16(a[8 * j], a[8 * j + 1])), "r"(pack_bf16(a[8 * j + 2], a[8 * j + 3])),
                         "r"(pack_bf16(a[8 * j + 4], a[8 * j + 5])), "r"(pack_bf16(a[8 * j + 6], a[8 * j + 7])), "r"(rbar) : "memory");
      } else {
        uint32_t z[16];
#pragma unroll
        for (int j = 0; j < 16; j++) z[j] = pack_bf16(a[2 * j], a[2 * j + 1]);
        mbar_wait(xfull0 + 8 * w, k & 1);
        FSTAMP(20);
        {
          uint32_t x[16];
          load_tile(x, xb);
#pragma unroll
          for (int j = 0; j < 16; j++) z[j] = add_bf16x2(z[j], x[j]);
#pragma unroll
          for (int j = 0; j < 16; j += 4) z[j] = (z[j] & ~1u) | tag;
        }
        if (k < 2) {
          if (wt == 0) mbar_expect_tx(xfull0 + 8 * w, XBUF_BYTES);
          fence_regs(z);
          __syncwarp();
          if (lane == 0) mbar_arrive_cluster(mapa(xempty0 + 8 * w, r ^ 1));
        }
        FSTAMP(21);
        if (k < 4) {
          const uint32_t st = k < 2 ? oslot_addr(sbase, 2 * t) + w * XBUF_BYTES + wt * 16 : xb;
#pragma unroll
          for (int j = 0; j < 4; j++)
            asm volatile("st.shared.v4.b32 [%0], {%1, %2, %3, %4};"
                         ::"r"(st + j * 2048), "r"(z[4 * j]), "r"(z[4 * j + 1]), "r"(z[4 * j + 2]), "r"(z[4 * j + 3]) : "memory");
          __syncwarp();
          if (lane == 0) mbar_arrive(ready0 + 24 * k + 8 * w);
        } else {
          const int c = chunk_of(ci, off), pos = pos_of(ci, c);
          uint4* dst = g_part + (size_t)((grp * 10 + c) * 7 + pos) * (SLOT_BYTES / 16) + w * 512 + wt;
#pragma unroll
          for (int j = 0; j < 4; j++)
            asm volatile("st.relaxed.gpu.global.v4.b32 [%0], {%1, %2, %3, %4};"
                         ::"l"(dst + j * 128), "r"(z[4 * j]), "r"(z[4 * j + 1]), "r"(z[4 * j + 2]), "r"(z[4 * j + 3]) : "memory");
        }
        FSTAMP(22);
      }
      ESTAMP(20 + t);
      FSTAMP(23);
    };
    auto finalize = [&]() {
      const int c = chunk_of(8 + r, off);
      TSTAMP(7);
      const uint4* tiles = g_part + (size_t)(grp * 10 + c) * 7 * (SLOT_BYTES / 16) + w * 512 + wt;
      auto load_g = [&](uint32_t (&y)[16], int q) {
#pragma unroll
        for (int j = 0; j < 4; j++)
          asm volatile("ld.relaxed.gpu.global.v4.b32 {%0, %1, %2, %3}, [%4];"
                       : "=r"(y[4 * j]), "=r"(y[4 * j + 1]), "=r"(y[4 * j + 2]), "=r"(y[4 * j + 3])
                       : "l"(tiles + q * (SLOT_BYTES / 16) + j * 128) : "memory");
      };
      const uint32_t toff = w * XBUF_BYTES + wt * 16;
      const uint32_t tm = tag - 1u;
      const uint32_t t0 = clk32();
      auto settle = [&](uint32_t (&y)[16], int q) {
        while (true) {
          if (tile_ok(y, tm) || clk32() - t0 > SPIN_LIMIT) break;
          load_g(y, q);
        }
        add_tile(a, y);

      };
      mbar_wait(fullo0 + 8 * 4, 0);
      uint32_t ok = 1u;
#pragma unroll
      for (int j = 0; j < 4; j++) {
        uint32_t x[4][4];
#pragma unroll
        for (int q = 0; q < 4; q++)
          asm volatile("ld.shared.v4.b32 {%0, %1, %2, %3}, [%4];"
                       : "=r"(x[q][0]), "=r"(x[q][1]), "=r"(x[q][2]), "=r"(x[q][3]) : "r"(oslot_addr(sbase, 4 + q) + toff + j * 2048) : "memory");
        ok = lop3<0x80>(ok, lop3<0x42>(x[0][0], x[1][0], tm), lop3<0x42>(x[2][0], x[3][0], tm));
#pragma unroll
        for (int i = 0; i < 4; i++) {
          const uint32_t u = add_bf16x2(x[0][i], x[1][i]), v = add_bf16x2(x[2][i], x[3][i]);
          const uint32_t s = add_bf16x2(u, v);
          a[8 * j + 2 * i] = __uint_as_float(s << 16);
          a[8 * j + 2 * i + 1] = __uint_as_float(s & 0xffff0000u);
        }
      }
      if (!ok) {
#pragma unroll
        for (int j = 0; j < 32; j++) a[j] = 0.f;
#pragma unroll 1
        for (int q = 0; q < 4; q++) {
          uint32_t x[16];
          load_g(x, q);
          settle(x, q);
        }
      }
      fence_regs(a);
      TSTAMP(30);
      mbar_wait(fullo0 + 8 * 2, 0);
      mbar_wait(fullo0 + 8 * 3, 0);
      asm volatile("bar.sync %0, 256;" ::"r"(1 + w) : "memory");
      wg_fence();
      {
        const uint64_t db = make_desc(oslot_addr(sbase, 2), 16, 1024);
#pragma unroll
        for (int j = 0; j < 12; j++) wgmma_n64_rs_tb(a, o0[4 * j], o0[4 * j + 1], o0[4 * j + 2], o0[4 * j + 3], db + 128 * j, 1);
        wg_commit();
      }
      {
        const uint64_t db = make_desc(oslot_addr(sbase, 3), 16, 1024);
#pragma unroll
        for (int j = 0; j < 12; j++) {
          wgmma_n64_rs_tb(a, o1[4 * j], o1[4 * j + 1], o1[4 * j + 2], o1[4 * j + 3], db + 128 * j, 1);
          if (j == TOKEN_AT && w < 2) asm volatile("bar.arrive %0, 256;" ::"r"(1 + wnext) : "memory");
        }
        wg_commit();
      }
      {
        uint32_t x[16], y0[16], y1[16], y2[16];
        wg_wait<1>();
        load_g(y0, 4); load_g(y1, 5); load_g(y2, 6);
        wg_wait<0>();
        fence_regs(a);
        TSTAMP(19);
        settle(y0, 4); settle(y1, 5); settle(y2, 6);
        fence_regs(a);
        TSTAMP(31);
        mbar_wait(xfull0 + 8 * w, 0); load_tile(x, xb);
        add_tile(a, x);
      }
      TSTAMP(8);
      const int row = tg * 192 + w * 64 + (wt >> 5) * 16 + ((wt >> 2) & 7);
      uint4* d0 = reinterpret_cast<uint4*>(out + (size_t)row * 1280 + p * 640 + c * 64 + (wt & 3) * 8);
      const bool b0 = wt & 1, b1 = wt & 2;
      __syncwarp();
#pragma unroll
      for (int u = 0; u < 4; u++) {
        uint32_t x[4];
#pragma unroll
        for (int i = 0; i < 4; i++) {
          const int j = (u & 1) * 4 + i;
          x[i] = pack_bf16(a[4 * j + (u >> 1) * 2], a[4 * j + (u >> 1) * 2 + 1]);
        }
        uint32_t v;
        v = __shfl_xor_sync(0xffffffffu, b0 ? x[0] : x[1], 1); if (b0) x[0] = v; else x[1] = v;
        v = __shfl_xor_sync(0xffffffffu, b0 ? x[2] : x[3], 1); if (b0) x[2] = v; else x[3] = v;
        v = __shfl_xor_sync(0xffffffffu, b1 ? x[0] : x[2], 2); if (b1) x[0] = v; else x[2] = v;
        v = __shfl_xor_sync(0xffffffffu, b1 ? x[1] : x[3], 2); if (b1) x[1] = v; else x[3] = v;
        d0[(u & 1) * 4 + (u >> 1) * 8 * 160] = make_uint4(x[0], x[1], x[2], x[3]);
      }
      if (hp == 1 && tid == 0) asm volatile("red.relaxed.gpu.global.add.u32 [%0], 1;" ::"l"(P.epoch + grp) : "memory");
    };
#pragma unroll 1
    for (int t = 0; t < 4; t++) {
      oproj_chunk<true>(a, o0, o1, t, w * XBUF_BYTES + wt * 16, sbase, fullo0, emptyo0, lane, w, wnext, true);
      TSTAMP(10 + t);
      epilogue(t);
    }
#pragma unroll 1
    for (int t = 4; t < 10; t++) {
      if (t == 9 && fin) { finalize(); break; }
      oproj_chunk<false>(a, o0, o1, t, 0, sbase, fullo0, emptyo0, lane, w, wnext, t < 9 || w < 2);
      TSTAMP(10 + t);
      epilogue(t);
    }
    TSTAMP(9);
    __syncwarp();
    TDUMP();
  }
}

typedef CUresult (*EncodeFn)(CUtensorMap*, CUtensorMapDataType, cuuint32_t, void*, const cuuint64_t*, const cuuint64_t*,
                             const cuuint32_t*, const cuuint32_t*, CUtensorMapInterleave, CUtensorMapSwizzle,
                             CUtensorMapL2promotion, CUtensorMapFloatOOBfill);

static void encode(EncodeFn fn, CUtensorMap* m, const void* ptr, int rank, const cuuint64_t* dims, const cuuint64_t* strides,
                   const cuuint32_t* box) {
  cuuint32_t es[5] = {1, 1, 1, 1, 1};
  fn(m, CU_TENSOR_MAP_DATA_TYPE_BFLOAT16, (cuuint32_t)rank, const_cast<void*>(ptr), dims, strides, box, es,
     CU_TENSOR_MAP_INTERLEAVE_NONE, CU_TENSOR_MAP_SWIZZLE_128B, CU_TENSOR_MAP_L2_PROMOTION_L2_256B,
     CU_TENSOR_MAP_FLOAT_OOB_FILL_NONE);
}

}

extern "C" void kernel_launch(void* const* d_in, const int* in_sizes, int n_in, void* d_out, int out_size) {
  using namespace fk;
  static Params params;
  static const void* cached[10] = {nullptr};
  static EncodeFn fn = nullptr;
  if (!fn) {
    void* f = nullptr;
    cudaDriverEntryPointQueryResult st;
    cudaGetDriverEntryPoint("cuTensorMapEncodeTiled", &f, cudaEnableDefault, &st);
    fn = (EncodeFn)f;
    void* e = nullptr;
    cudaGetSymbolAddress(&e, g_epoch);
    params.epoch = (unsigned int*)e;
    cudaFuncSetAttribute(fused_kernel, cudaFuncAttributeMaxDynamicSharedMemorySize, SMEM_BYTES);
  }
  bool same = true;
  for (int i = 0; i < 10; i++) same = same && (cached[i] == d_in[i]);
  if (!same) {
    for (int p = 0; p < 2; p++) {
      const void* x = d_in[5 * p + 0];
      const void* k = d_in[5 * p + 1];
      const void* v = d_in[5 * p + 2];
      const void* wq = d_in[5 * p + 3];
      const void* wo = d_in[5 * p + 4];
      params.kp[p] = (const char*)k; params.vp[p] = (const char*)v;
      params.wqp[p] = (const char*)wq; params.xp[p] = (const char*)x;
      {
        cuuint64_t d[2] = {640, 768}, s[1] = {1280};
        cuuint32_t b[2] = {64, 96};
        encode(fn, &params.x[p], x, 2, d, s, b);
      }
      {
        cuuint64_t d[3] = {64, 640, 96}, s[2] = {12288, 128};
        cuuint32_t b[3] = {64, 64, 3};
        encode(fn, &params.wq[p], wq, 3, d, s, b);
      }
      {
        cuuint64_t d[4] = {192, 48, 32, 16}, s[3] = {384, 18432, 589824};
        cuuint32_t b[4] = {64, 48, 1, 4};
        encode(fn, &params.k[p], k, 4, d, s, b);
        encode(fn, &params.v[p], v, 4, d, s, b);
      }
      {
        cuuint64_t d[2] = {640, 6144}, s[1] = {1280};
        cuuint32_t b[2] = {64, 192};
        encode(fn, &params.wo[p], wo, 2, d, s, b);
      }
    }
    for (int i = 0; i < 10; i++) cached[i] = d_in[i];
  }
  fused_kernel<<<128, NTHREADS, SMEM_BYTES>>>(params, (__nv_bfloat16*)d_out);
}
```

```cpp
#include <cuda_runtime.h>
#include <cuda_bf16.h>
#include <cuda.h>
#include <stdint.h>

#define PF_ON 1
#define PF_WIN 4
#define PF_WIN1 4
#define PF_WIN0 3
#define FDELAY 500
#define FDELAY_C 1
#define GATHB 0
#define DEFER 0
#define PRE3 1
#define YFIRST 1
#define PACE 485
#define PF_TRIG 3
#define PF0_FROM 5
#define PF_NW 2
#define PF0 1
#define QMMA 4
#define TOKEN_AT 8
#define TOKEN_S 8
#define SPIN_LIMIT (1u << 27)

namespace fk {

#define HEADMAP 0
constexpr int HM = HEADMAP ? 1 : 2, HS = HEADMAP ? 16 : 1;
constexpr int SLOT_BYTES = 24576;
constexpr int NSLOT = 9;
constexpr int XBUF_BYTES = 8192;
constexpr int XBUF_OFF = 8 * SLOT_BYTES;
constexpr int BAR_OFF = NSLOT * SLOT_BYTES;
constexpr int FULLO = 192, FULLE = 272, EMPTYE = 360;
constexpr int SINK_OFF = BAR_OFF + 1024;
constexpr int PF_DEPTH = 9;
constexpr int SMEM_BYTES = SINK_OFF + PF_DEPTH * 960 + 1024;
constexpr int NTHREADS = 512;

struct Params {
  CUtensorMap x[2], wq[2], k[2], v[2], wo[2];
  const char* kp[2]; const char* vp[2]; const char* wqp[2]; const char* xp[2];
  unsigned int* epoch;
};

__device__ uint4 g_part[8 * 10 * 7 * (SLOT_BYTES / 16)];
__device__ unsigned int g_epoch[8];
#define TSTAMP(i)
#define PSTAMP(i)
#define HSTAMP(i)
#define GSTAMP(a, b)
#define HSTAMP2(i)
#define CSTAMP(i)
#define TDUMP()

#define XSTAMP(i)
#define ESTAMP(i) TSTAMP(i)
#define QSTAMP(i)
#define FSTAMP(i)
#define SNOW(v)
#define SPUT(i, v)
__device__ __forceinline__ uint32_t smem_u32(const void* p) { return (uint32_t)__cvta_generic_to_shared(p); }
__device__ __forceinline__ void mbar_init(uint32_t bar, uint32_t cnt) {
  asm volatile("mbarrier.init.shared::cta.b64 [%0], %1;" ::"r"(bar), "r"(cnt) : "memory");
}
__device__ __forceinline__ void mbar_expect_tx(uint32_t bar, uint32_t bytes) {
  asm volatile("mbarrier.arrive.expect_tx.shared::cta.b64 _, [%0], %1;" ::"r"(bar), "r"(bytes) : "memory");
}
__device__ __forceinline__ uint32_t mapa(uint32_t addr, uint32_t cta) {
  uint32_t r;
  asm volatile("mapa.shared::cluster.u32 %0, %1, %2;" : "=r"(r) : "r"(addr), "r"(cta));
  return r;
}
__device__ __forceinline__ void mbar_arrive_cluster(uint32_t remote_bar) {
  asm volatile("mbarrier.arrive.shared::cluster.b64 _, [%0];" ::"r"(remote_bar) : "memory");
}
__device__ __forceinline__ uint32_t mbar_try(uint32_t bar, uint32_t parity) {
  uint32_t ok;
  asm volatile("{\n.reg .pred p;\nmbarrier.try_wait.parity.shared::cta.b64 p, [%1], %2;\nselp.u32 %0, 1, 0, p;\n}\n"
               : "=r"(ok) : "r"(bar), "r"(parity) : "memory");
  return ok;
}
__device__ __forceinline__ uint32_t mbar_test(uint32_t bar, uint32_t parity) {
  uint32_t ok;
  asm volatile("{\n.reg .pred p;\nmbarrier.test_wait.parity.shared::cta.b64 p, [%1], %2;\nselp.u32 %0, 1, 0, p;\n}\n"
               : "=r"(ok) : "r"(bar), "r"(parity) : "memory");
  return ok;
}
__device__ __forceinline__ uint32_t mbar_try_cluster(uint32_t bar, uint32_t parity) {
  uint32_t ok;
  asm volatile("{\n.reg .pred p;\nmbarrier.try_wait.parity.acquire.cluster.shared::cta.b64 p, [%1], %2;\nselp.u32 %0, 1, 0, p;\n}\n"
               : "=r"(ok) : "r"(bar), "r"(parity) : "memory");
  return ok;
}
__device__ __forceinline__ uint32_t clk32() {
  uint32_t t;
  asm volatile("mov.u32 %0, %%clock;" : "=r"(t));
  return t;
}
#define DBGREC(a, b)
__device__ __forceinline__ void mbar_wait(uint32_t bar, uint32_t parity) {
  if (mbar_try(bar, parity)) return;
  const uint32_t t0 = clk32();
  while (!mbar_try(bar, parity)) {
    if (clk32() - t0 > SPIN_LIMIT) { DBGREC(bar, parity); break; }
  }
}
__device__ __forceinline__ void mbar_wait_cluster(uint32_t bar, uint32_t parity) {
  if (mbar_try_cluster(bar, parity)) return;
  const uint32_t t0 = clk32();
  while (!mbar_try_cluster(bar, parity)) {
    if (clk32() - t0 > SPIN_LIMIT) break;
  }
}
__device__ __forceinline__ void cluster_sync() {
  asm volatile("barrier.cluster.arrive.release.aligned;\nbarrier.cluster.wait.acquire.aligned;\n" ::: "memory");
}
__device__ __forceinline__ void tma2d(uint32_t dst, const CUtensorMap* m, int c0, int c1, uint32_t bar) {
  asm volatile("cp.async.bulk.tensor.2d.shared::cluster.global.mbarrier::complete_tx::bytes [%0], [%1, {%3, %4}], [%2];"
               ::"r"(dst), "l"(m), "r"(bar), "r"(c0), "r"(c1) : "memory");
}
__device__ __forceinline__ void tma2d_mc(uint32_t dst, const CUtensorMap* m, int c0, int c1, uint32_t bar, uint16_t mask) {
  asm volatile("cp.async.bulk.tensor.2d.shared::cluster.global.mbarrier::complete_tx::bytes.multicast::cluster [%0], [%1, {%3, %4}], [%2], %5;"
               ::"r"(dst), "l"(m), "r"(bar), "r"(c0), "r"(c1), "h"(mask) : "memory");
}
__device__ __forceinline__ void tma3d(uint32_t dst, const CUtensorMap* m, int c0, int c1, int c2, uint32_t bar) {
  asm volatile("cp.async.bulk.tensor.3d.shared::cluster.global.mbarrier::complete_tx::bytes [%0], [%1, {%3, %4, %5}], [%2];"
               ::"r"(dst), "l"(m), "r"(bar), "r"(c0), "r"(c1), "r"(c2) : "memory");
}
__device__ __forceinline__ void tma4d(uint32_t dst, const CUtensorMap* m, int c0, int c1, int c2, int c3, uint32_t bar) {
  asm volatile("cp.async.bulk.tensor.4d.shared::cluster.global.mbarrier::complete_tx::bytes [%0], [%1, {%3, %4, %5, %6}], [%2];"
               ::"r"(dst), "l"(m), "r"(bar), "r"(c0), "r"(c1), "r"(c2), "r"(c3) : "memory");
}
__device__ __forceinline__ void mbar_arrive(uint32_t bar) {
  asm volatile("mbarrier.arrive.shared::cta.b64 _, [%0];" ::"r"(bar) : "memory");
}
__device__ __forceinline__ uint32_t touch_l2(const void* p) {
  uint32_t v;
  asm volatile("ld.global.cg.L2::128B.b32 %0, [%1];" : "=r"(v) : "l"(p));
  return v;
}
__device__ __forceinline__ unsigned ld_acquire(const unsigned* p) {
  unsigned v;
  asm volatile("ld.acquire.gpu.global.u32 %0, [%1];" : "=r"(v) : "l"(p) : "memory");
  return v;
}
__device__ __forceinline__ void wg_fence() { asm volatile("wgmma.fence.sync.aligned;" ::: "memory"); }
__device__ __forceinline__ void wg_commit() { asm volatile("wgmma.commit_group.sync.aligned;" ::: "memory"); }
template <int N> __device__ __forceinline__ void wg_wait() { asm volatile("wgmma.wait_group.sync.aligned %0;" ::"n"(N) : "memory"); }
template <int N> __device__ __forceinline__ void fence_regs(float (&d)[N]) {
#pragma unroll
  for (int i = 0; i < N; i++) asm volatile("" : "+f"(d[i])::"memory");
}
template <int N> __device__ __forceinline__ void fence_regs(uint32_t (&d)[N]) {
#pragma unroll
  for (int i = 0; i < N; i++) asm volatile("" : "+r"(d[i])::"memory");
}
template <int N> __device__ __forceinline__ void pin_regs(const uint32_t* d, uint32_t never, uint32_t addr) {
#pragma unroll
  for (int i = 0; i < N; i += 4)
    asm volatile("{\n.reg .pred p;\nsetp.ne.u32 p, %5, 0;\n@p st.shared.v4.b32 [%0], {%1, %2, %3, %4};\n}\n"
                 ::"r"(addr), "r"(d[i]), "r"(d[i + 1]), "r"(d[i + 2]), "r"(d[i + 3]), "r"(never) : "memory");
}
__device__ __forceinline__ uint32_t pack_bf16(float lo, float hi) {
  uint32_t r;
  asm("cvt.rn.bf16x2.f32 %0, %1, %2;" : "=r"(r) : "f"(hi), "f"(lo));
  return r;
}
__device__ __forceinline__ float ex2(float x) {
  float r;
  asm("ex2.approx.ftz.f32 %0, %1;" : "=f"(r) : "f"(x));
  return r;
}
__device__ __forceinline__ float rcp(float x) {
  float r;
  asm("rcp.approx.ftz.f32 %0, %1;" : "=f"(r) : "f"(x));
  return r;
}
__device__ __forceinline__ uint64_t make_desc(uint32_t addr, uint32_t lbo, uint32_t sbo) {
  return (uint64_t)((addr & 0x3FFFFu) >> 4) | ((uint64_t)(lbo >> 4) << 16) | ((uint64_t)(sbo >> 4) << 32) | (1ull << 62);
}

__device__ __forceinline__ void wgmma_n192_ss_tb(float (&d)[96], uint64_t da, uint64_t db, int scale_d) {
  asm volatile("{\n.reg .pred p;\nsetp.ne.b32 p, %98, 0;\n"
    "wgmma.mma_async.sync.aligned.m64n192k16.f32.bf16.bf16 "
    "{%0, %1, %2, %3, %4, %5, %6, %7, %8, %9, %10, %11, %12, %13, %14, %15, %16, %17, %18, %19, %20, %21, %22, %23, %24, %25, %26, %27, %28, %29, %30, %31, %32, %33, %34, %35, %36, %37, %38, %39, %40, %41, %42, %43, %44, %45, %46, %47, %48, %49, %50, %51, %52, %53, %54, %55, %56, %57, %58, %59, %60, %61, %62, %63, %64, %65, %66, %67, %68, %69, %70, %71, %72, %73, %74, %75, %76, %77, %78, %79, %80, %81, %82, %83, %84, %85, %86, %87, %88, %89, %90, %91, %92, %93, %94, %95}, "
    "%96, %97, p, 1, 1, 0, 1;\n}\n"
    : "+f"(d[0]), "+f"(d[1]), "+f"(d[2]), "+f"(d[3]), "+f"(d[4]), "+f"(d[5]), "+f"(d[6]), "+f"(d[7]), "+f"(d[8]), "+f"(d[9]), "+f"(d[10]), "+f"(d[11]), "+f"(d[12]), "+f"(d[13]), "+f"(d[14]), "+f"(d[15]), "+f"(d[16]), "+f"(d[17]), "+f"(d[18]), "+f"(d[19]), "+f"(d[20]), "+f"(d[21]), "+f"(d[22]), "+f"(d[23]), "+f"(d[24]), "+f"(d[25]), "+f"(d[26]), "+f"(d[27]), "+f"(d[28]), "+f"(d[29]), "+f"(d[30]), "+f"(d[31]), "+f"(d[32]), "+f"(d[33]), "+f"(d[34]), "+f"(d[35]), "+f"(d[36]), "+f"(d[37]), "+f"(d[38]), "+f"(d[39]), "+f"(d[40]), "+f"(d[41]), "+f"(d[42]), "+f"(d[43]), "+f"(d[44]), "+f"(d[45]), "+f"(d[46]), "+f"(d[47]), "+f"(d[48]), "+f"(d[49]), "+f"(d[50]), "+f"(d[51]), "+f"(d[52]), "+f"(d[53]), "+f"(d[54]), "+f"(d[55]), "+f"(d[56]), "+f"(d[57]), "+f"(d[58]), "+f"(d[59]), "+f"(d[60]), "+f"(d[61]), "+f"(d[62]), "+f"(d[63]), "+f"(d[64]), "+f"(d[65]), "+f"(d[66]), "+f"(d[67]), "+f"(d[68]), "+f"(d[69]), "+f"(d[70]), "+f"(d[71]), "+f"(d[72]), "+f"(d[73]), "+f"(d[74]), "+f"(d[75]), "+f"(d[76]), "+f"(d[77]), "+f"(d[78]), "+f"(d[79]), "+f"(d[80]), "+f"(d[81]), "+f"(d[82]), "+f"(d[83]), "+f"(d[84]), "+f"(d[85]), "+f"(d[86]), "+f"(d[87]), "+f"(d[88]), "+f"(d[89]), "+f"(d[90]), "+f"(d[91]), "+f"(d[92]), "+f"(d[93]), "+f"(d[94]), "+f"(d[95])
    : "l"(da), "l"(db), "r"(scale_d));
}
__device__ __forceinline__ void wgmma_n96_rs(float (&d)[48], uint32_t a0, uint32_t a1, uint32_t a2, uint32_t a3, uint64_t db, int scale_d) {
  asm volatile("{\n.reg .pred p;\nsetp.ne.b32 p, %53, 0;\n"
    "wgmma.mma_async.sync.aligned.m64n96k16.f32.bf16.bf16 "
    "{%0, %1, %2, %3, %4, %5, %6, %7, %8, %9, %10, %11, %12, %13, %14, %15, %16, %17, %18, %19, %20, %21, %22, %23, %24, %25, %26, %27, %28, %29, %30, %31, %32, %33, %34, %35, %36, %37, %38, %39, %40, %41, %42, %43, %44, %45, %46, %47}, "
    "{%48, %49, %50, %51}, %52, p, 1, 1, 0;\n}\n"
    : "+f"(d[0]), "+f"(d[1]), "+f"(d[2]), "+f"(d[3]), "+f"(d[4]), "+f"(d[5]), "+f"(d[6]), "+f"(d[7]), "+f"(d[8]), "+f"(d[9]), "+f"(d[10]), "+f"(d[11]), "+f"(d[12]), "+f"(d[13]), "+f"(d[14]), "+f"(d[15]), "+f"(d[16]), "+f"(d[17]), "+f"(d[18]), "+f"(d[19]), "+f"(d[20]), "+f"(d[21]), "+f"(d[22]), "+f"(d[23]), "+f"(d[24]), "+f"(d[25]), "+f"(d[26]), "+f"(d[27]), "+f"(d[28]), "+f"(d[29]), "+f"(d[30]), "+f"(d[31]), "+f"(d[32]), "+f"(d[33]), "+f"(d[34]), "+f"(d[35]), "+f"(d[36]), "+f"(d[37]), "+f"(d[38]), "+f"(d[39]), "+f"(d[40]), "+f"(d[41]), "+f"(d[42]), "+f"(d[43]), "+f"(d[44]), "+f"(d[45]), "+f"(d[46]), "+f"(d[47])
    : "r"(a0), "r"(a1), "r"(a2), "r"(a3), "l"(db), "r"(scale_d));
}
__device__ __forceinline__ void wgmma_n64_rs_tb(float (&d)[32], uint32_t a0, uint32_t a1, uint32_t a2, uint32_t a3, uint64_t db, int scale_d) {
  asm volatile("{\n.reg .pred p;\nsetp.ne.b32 p, %37, 0;\n"
    "wgmma.mma_async.sync.aligned.m64n64k16.f32.bf16.bf16 "
    "{%0, %1, %2, %3, %4, %5, %6, %7, %8, %9, %10, %11, %12, %13, %14, %15, %16, %17, %18, %19, %20, %21, %22, %23, %24, %25, %26, %27, %28, %29, %30, %31}, "
    "{%32, %33, %34, %35}, %36, p, 1, 1, 1;\n}\n"
    : "+f"(d[0]), "+f"(d[1]), "+f"(d[2]), "+f"(d[3]), "+f"(d[4]), "+f"(d[5]), "+f"(d[6]), "+f"(d[7]), "+f"(d[8]), "+f"(d[9]), "+f"(d[10]), "+f"(d[11]), "+f"(d[12]), "+f"(d[13]), "+f"(d[14]), "+f"(d[15]), "+f"(d[16]), "+f"(d[17]), "+f"(d[18]), "+f"(d[19]), "+f"(d[20]), "+f"(d[21]), "+f"(d[22]), "+f"(d[23]), "+f"(d[24]), "+f"(d[25]), "+f"(d[26]), "+f"(d[27]), "+f"(d[28]), "+f"(d[29]), "+f"(d[30]), "+f"(d[31])
    : "r"(a0), "r"(a1), "r"(a2), "r"(a3), "l"(db), "r"(scale_d));
}

__device__ __forceinline__ int chunk_of(int i, int off) { const int c = i + off; return c >= 10 ? c - 10 : c; }
__device__ __forceinline__ int pos_of(int i, int c) { return i - (i > chunk_of(c, 6)) - (i > chunk_of(c, 1)); }
__device__ __forceinline__ int index_at(int t, int r, bool fin) { return (r == 0 && (t < 8 || fin)) ? (t ^ 1) : t; }

constexpr int KPOS = 43;
__device__ __forceinline__ void do_item(const Params& P, int i, int p, int tg, int h0, int r, uint32_t dst, uint32_t bar) {
  if (i >= 46) {
    const int h1 = i >= 49;
    tma4d(dst, &P.v[p], (i - 46 - 3 * h1) * 64, 0, h0 + HS * h1, tg * 4, bar);
  } else if (i >= KPOS && i < KPOS + 3) {
    tma4d(dst, &P.k[p], (i - KPOS) * 64, 0, h0 + HS, tg * 4, bar);
  } else if (i >= 20 && i < 23) {
    tma4d(dst, &P.k[p], (i - 20) * 64, 0, h0, tg * 4, bar);
  } else {
    const int hh = i >= 23;
    const int j = i - 23 * hh - 3 * (i >= KPOS);
    const int kc = j >> 1;
    if (!(j & 1)) tma2d_mc(dst + r * 12288, &P.x[p], kc * 64, tg * 192 + r * 96, bar, (uint16_t)3);
    else tma3d(dst, &P.wq[p], 0, kc * 64, (h0 + HS * hh) * 3, bar);
  }
}

struct Ring {
  uint32_t slot, phase;
  __device__ __forceinline__ void advance() {
    if (++slot == NSLOT) { slot = 0; phase ^= 1; }
  }
};

__device__ __forceinline__ void load_tile(uint32_t (&x)[16], uint32_t addr) {
#pragma unroll
  for (int j = 0; j < 4; j++)
    asm volatile("ld.shared.v4.b32 {%0, %1, %2, %3}, [%4];"
                 : "=r"(x[4 * j]), "=r"(x[4 * j + 1]), "=r"(x[4 * j + 2]), "=r"(x[4 * j + 3]) : "r"(addr + j * 2048) : "memory");
}
__device__ __forceinline__ void store_tile(uint32_t addr, const float (&a)[32]) {
#pragma unroll
  for (int j = 0; j < 4; j++)
    asm volatile("st.shared.v4.b32 [%0], {%1, %2, %3, %4};"
                 ::"r"(addr + j * 2048), "r"(pack_bf16(a[8 * j], a[8 * j + 1])), "r"(pack_bf16(a[8 * j + 2], a[8 * j + 3])),
                   "r"(pack_bf16(a[8 * j + 4], a[8 * j + 5])), "r"(pack_bf16(a[8 * j + 6], a[8 * j + 7])) : "memory");
}
__device__ __forceinline__ uint32_t add_bf16x2(uint32_t a, uint32_t b) {
  uint32_t r;
  asm("add.rn.bf16x2 %0, %1, %2;" : "=r"(r) : "r"(a), "r"(b));
  return r;
}
template <int LUT> __device__ __forceinline__ uint32_t lop3(uint32_t a, uint32_t b, uint32_t c) {
  uint32_t r;
  asm("lop3.b32 %0, %1, %2, %3, %4;" : "=r"(r) : "r"(a), "r"(b), "r"(c), "n"(LUT));
  return r;
}
__device__ __forceinline__ uint32_t tile_ok(const uint32_t (&y)[16], uint32_t tm) {
  return (y[0] ^ tm) & (y[4] ^ tm) & (y[8] ^ tm) & (y[12] ^ tm) & 1u;
}
__device__ __forceinline__ void add_tile(float (&a)[32], const uint32_t (&x)[16]) {
#pragma unroll
  for (int j = 0; j < 16; j++) {
    a[2 * j] += __uint_as_float(x[j] << 16);
    a[2 * j + 1] += __uint_as_float(x[j] & 0xffff0000u);
  }
}
__device__ __forceinline__ uint32_t oslot(uint32_t j) { return (uint32_t)(0x83d65683d6541d9ull >> (3 * j)) & 7u; }

struct Front {
  Ring rg;
  uint32_t sbase, full0, rel0, never;
  int w, lane, hf;
  __device__ __forceinline__ uint32_t tsb() const { return full0 + 512 + w * 128; }
  __device__ __forceinline__ void release(uint32_t s) const { if (lane < 2) mbar_arrive_cluster(rel0 + 8 * s); }
  __device__ __forceinline__ uint32_t next() {
    const uint32_t s = rg.slot;
    mbar_wait(full0 + 8 * s, rg.phase);
    rg.advance();
    return s;
  }
  template <bool FIRST> __device__ __forceinline__ void qchunk(float (&acc)[96], uint32_t& sx, uint32_t& sw) {
    sx = next(); sw = next();
    const uint64_t da = make_desc(sbase + sx * SLOT_BYTES + w * 8192, 16, 1024);
    const uint64_t db = make_desc(sbase + sw * SLOT_BYTES, 8192, 1024);
    wg_fence();
#pragma unroll
    for (int s = 0; s < QMMA; s++) wgmma_n192_ss_tb(acc, da + 2 * s, db + 128 * s, !FIRST || s != 0);
    wg_commit();
  }
  __device__ __forceinline__ void qrest(float (&acc)[96], uint32_t (&qf)[48], uint32_t psx, uint32_t psw, int kc0, int tbase) {
#pragma unroll 1
    for (int kc = kc0; kc < 10; kc++) {
      uint32_t sx, sw;
      qchunk<false>(acc, sx, sw);
      QSTAMP(20 + kc);
      wg_wait<1>(); release(psx); release(psw);
      psx = sx; psw = sw;
    }
    wg_wait<0>();
    fence_regs(acc);
    release(psx); release(psw);
#pragma unroll
    for (int i = 24; i < 48; i++) qf[i] = pack_bf16(acc[2 * i], acc[2 * i + 1]);
    pin_regs<24>(qf + 24, never, full0);
#pragma unroll
    for (int i = 0; i < 24; i++) qf[i] = pack_bf16(acc[2 * i], acc[2 * i + 1]);
    pin_regs<24>(qf, never, full0);
    fence_regs(qf);
  }
  __device__ __forceinline__ void scores(float (&v)[24], const uint32_t (&qf)[48]) {
    float sacc[48];
    uint32_t ks[3];
#pragma unroll
    for (int dc = 0; dc < 3; dc++) {
      ks[dc] = next();
      const uint64_t db = make_desc(sbase + ks[dc] * SLOT_BYTES + w * 6144, 16, 1024);
      wg_fence();
#pragma unroll
      for (int s = 0; s < 4; s++) {
        const int j = dc * 4 + s;
        wgmma_n96_rs(sacc, qf[4 * j], qf[4 * j + 1], qf[4 * j + 2], qf[4 * j + 3], db + 2 * s, j != 0);
      }
    }
    wg_commit();
    wg_wait<0>();
    fence_regs(sacc);
    release(ks[0]); release(ks[1]); release(ks[2]);
#pragma unroll
    for (int i = 0; i < 24; i++) v[i] = hf ? sacc[24 + i] : sacc[i];
    fence_regs(v);
  }
  __device__ __forceinline__ void softmax(uint32_t (&pk)[12], float (&v)[24]) {
    float m0 = v[0], m1 = v[2];
#pragma unroll
    for (int t = 0; t < 6; t++) {
      m0 = fmaxf(m0, fmaxf(v[4 * t], v[4 * t + 1]));
      m1 = fmaxf(m1, fmaxf(v[4 * t + 2], v[4 * t + 3]));
    }
    m0 = fmaxf(m0, __shfl_xor_sync(0xffffffffu, m0, 1));
    m1 = fmaxf(m1, __shfl_xor_sync(0xffffffffu, m1, 1));
    m0 = fmaxf(m0, __shfl_xor_sync(0xffffffffu, m0, 2));
    m1 = fmaxf(m1, __shfl_xor_sync(0xffffffffu, m1, 2));
    const float cs = 0.07216878364870322f * 1.4426950408889634f;
    const float b0 = m0 * cs, b1 = m1 * cs;
    float s0 = 0.f, s1 = 0.f;
#pragma unroll
    for (int t = 0; t < 6; t++) {
      v[4 * t] = ex2(fmaf(v[4 * t], cs, -b0));
      v[4 * t + 1] = ex2(fmaf(v[4 * t + 1], cs, -b0));
      v[4 * t + 2] = ex2(fmaf(v[4 * t + 2], cs, -b1));
      v[4 * t + 3] = ex2(fmaf(v[4 * t + 3], cs, -b1));
      s0 += v[4 * t] + v[4 * t + 1];
      s1 += v[4 * t + 2] + v[4 * t + 3];
    }
    s0 += __shfl_xor_sync(0xffffffffu, s0, 1);
    s1 += __shfl_xor_sync(0xffffffffu, s1, 1);
    s0 += __shfl_xor_sync(0xffffffffu, s0, 2);
    s1 += __shfl_xor_sync(0xffffffffu, s1, 2);
    const float r0 = rcp(s0), r1 = rcp(s1);
#pragma unroll
    for (int t = 0; t < 6; t++) {
      pk[2 * t] = pack_bf16(v[4 * t] * r0, v[4 * t + 1] * r0);
      pk[2 * t + 1] = pack_bf16(v[4 * t + 2] * r1, v[4 * t + 3] * r1);
    }
    pin_regs<12>(pk, never, full0);
    fence_regs(pk);
  }
  __device__ __forceinline__ void expand(uint32_t (&pa)[24], uint32_t (&pk)[12]) {
    fence_regs(pk);
#pragma unroll
    for (int i = 0; i < 12; i++) {
      pa[i] = hf ? 0u : pk[i];
      pa[12 + i] = hf ? pk[i] : 0u;
    }
    fence_regs(pa);
  }
  __device__ __forceinline__ void pv(float (&oa)[32], const uint32_t (&pa)[24], int s, int parity) {
    mbar_wait(full0 + 8 * s, parity);
    const uint64_t db = make_desc(sbase + s * SLOT_BYTES + w * 6144, 16, 1024);
    wg_fence();
#pragma unroll
    for (int j = 0; j < 6; j++) wgmma_n64_rs_tb(oa, pa[4 * j], pa[4 * j + 1], pa[4 * j + 2], pa[4 * j + 3], db + 128 * j, j != 0);
  }
  __device__ __forceinline__ void pack16(uint32_t* o, const float (&oa)[32]) {
#pragma unroll
    for (int i = 0; i < 16; i++) o[i] = pack_bf16(oa[2 * i], oa[2 * i + 1]);
    pin_regs<16>(o, never, full0);
  }
  __device__ __forceinline__ void early(float (&a)[32], const uint32_t (&o0)[48], int t) {
    mbar_wait(full0 + FULLE + 8 * t, 0);
    const uint64_t db = make_desc(sbase + (4 + t) * SLOT_BYTES, 16, 1024);
    wg_fence();
#pragma unroll
    for (int j = 0; j < 12; j++)
      wgmma_n64_rs_tb(a, o0[4 * j], o0[4 * j + 1], o0[4 * j + 2], o0[4 * j + 3], db + 128 * j, j != 0);
    wg_commit();
  }
  __device__ __forceinline__ void park(float (&a)[32], int t) {
    fence_regs(a);
    if (lane == 0) mbar_arrive(full0 + EMPTYE + 8 * (t + 1));
    mbar_wait(full0 + EMPTYE + 8 * t, 0);
    uint32_t tid;
    asm volatile("mov.u32 %0, %%tid.x;" : "=r"(tid));
    store_tile(sbase + oslot(4 * t) * SLOT_BYTES + (tid >> 7) * XBUF_BYTES + (tid & 127) * 16, a);
  }
  __device__ __forceinline__ void run(uint32_t (&o0)[48], uint32_t (&o1)[48]) {
    uint32_t pk[12], pa[24];
    float v[24];
    {
      uint32_t qf[48];
      {
        float acc[96];
        uint32_t sx, sw;
        qchunk<true>(acc, sx, sw);
        { const int tbase = 1; (void)tbase; QSTAMP(20); }
        qrest(acc, qf, sx, sw, 1, 1);
      }
      TSTAMP(1);
      scores(v, qf);
      TSTAMP(2);
    }
    {
      uint32_t qf[48];
      {
        float acc[96];
        uint32_t ax, aw, bx, bw;
        qchunk<true>(acc, ax, aw);
        qchunk<false>(acc, bx, bw);
        softmax(pk, v);
        TSTAMP(3);
        wg_wait<1>(); release(ax); release(aw);
        qrest(acc, qf, bx, bw, 2, 4);
      }
      TSTAMP(4);
      scores(v, qf);
      TSTAMP(5);
    }
    {
      float oa[32], ob[32], oc[32];
      expand(pa, pk);
      pv(oa, pa, 1, 1); pv(ob, pa, 2, 1); pv(oc, pa, 3, 1);
      wg_commit();
      XSTAMP(20);
      softmax(pk, v);
      XSTAMP(21);
      wg_wait<0>();
      fence_regs(oa); fence_regs(ob); fence_regs(oc);
      XSTAMP(22);
      release(2); release(3);
      if (lane == 0) mbar_arrive(full0 + EMPTYE);
      pack16(o0, oa); pack16(o0 + 16, ob); pack16(o0 + 32, oc);
      fence_regs(o0);
    }
    {
      float oa[32], ob[32];
      early(oa, o0, 0);
      early(ob, o0, 1);
      XSTAMP(23);
      wg_wait<1>(); park(oa, 0);
      early(oa, o0, 2);
      wg_wait<1>(); park(ob, 1);
      early(ob, o0, 3);
      XSTAMP(24);
      wg_wait<1>(); park(oa, 2);
      wg_wait<0>(); park(ob, 3);
      XSTAMP(25);
      fence_regs(o0);
#pragma unroll
      for (int i = 0; i < 12; i++) o0[i] += never;
      fence_regs(o0);
      expand(pa, pk);
      pv(oa, pa, 8, 1);
      pv(ob, pa, 0, 0);
      wg_commit();
      XSTAMP(26);
      wg_wait<0>();
      fence_regs(oa); fence_regs(ob);
      XSTAMP(27);
      release(8); release(0);
      pack16(o1, oa); pack16(o1 + 16, ob);
      float oc[32];
      pv(oc, pa, 2, 0);
      wg_commit();
      XSTAMP(28);
      wg_wait<0>();
      fence_regs(oc);
      release(2);
      pack16(o1 + 32, oc);
    }
    TSTAMP(6);
  }
};

__device__ __forceinline__ uint32_t oslot_addr(uint32_t sbase, uint32_t j) { return sbase + oslot(j) * SLOT_BYTES; }
template <bool EARLY, class Mid>
__device__ __forceinline__ void oproj_chunk(float (&a)[32], const uint32_t (&o0)[48], const uint32_t (&o1)[48], int t,
                                            uint32_t sbase, uint32_t fullo0, int w, int wnext, bool pass, Mid mid) {
  mbar_wait(fullo0 + 8 * t, 0);
  asm volatile("bar.sync %0, 256;" ::"r"(1 + w) : "memory");
  wg_fence();
  if (!EARLY) {
    const uint64_t db = make_desc(oslot_addr(sbase, 2 * t), 16, 1024);
#pragma unroll
    for (int j = 0; j < 12; j++)
      wgmma_n64_rs_tb(a, o0[4 * j], o0[4 * j + 1], o0[4 * j + 2], o0[4 * j + 3], db + 128 * j, j != 0);
  }
  {
    const uint64_t db = make_desc(oslot_addr(sbase, 2 * t + 1), 16, 1024);
#pragma unroll
    for (int j = 0; j < 12; j++) {
      wgmma_n64_rs_tb(a, o1[4 * j], o1[4 * j + 1], o1[4 * j + 2], o1[4 * j + 3], db + 128 * j, !EARLY || j != 0);
      if (j == (EARLY ? TOKEN_S : TOKEN_AT) && pass) asm volatile("bar.arrive %0, 256;" ::"r"(1 + wnext) : "memory");
    }
    wg_commit();
  }
  mid();
  wg_wait<0>();
  fence_regs(a);
}

__global__ void __cluster_dims__(2, 1, 1) __launch_bounds__(NTHREADS, 1)
fused_kernel(const __grid_constant__ Params P, __nv_bfloat16* __restrict__ out) {
  extern __shared__ uint8_t smem_raw[];
  const uint32_t sbase = (smem_u32(smem_raw) + 1023u) & ~1023u;
  const uint32_t full0 = sbase + BAR_OFF;
  const uint32_t empty0 = full0 + 72;
  const uint32_t xfull0 = full0 + 144;
  const uint32_t xempty0 = full0 + 168;
  const uint32_t fullo0 = full0 + FULLO;
  const uint32_t emptyo0 = full0 + 400;
  const uint32_t eready = full0 + 344;
  const uint32_t epoch_s = full0 + 352;
  const uint32_t emptye0 = full0 + EMPTYE;

  const int tid = threadIdx.x, lane = tid & 31;
  const int warp = __shfl_sync(0xffffffffu, tid >> 5, 0);
  auto tsb = [&]() { return full0 + 512 + (warp >> 2) * 128; };
  const int bid = blockIdx.x;
  const int hp = bid & 15, tg = (bid >> 4) & 3, p = bid >> 6;
  const int r = hp & 1;
  const int h0 = hp * HM;
  const int grp = p * 4 + tg;
  const int off = (hp >> 1) + (hp >> 3);
  const bool fin = r == 1 || off == 0 || off == 5;

  if (warp >= 12) {
    asm volatile("setmaxnreg.dec.sync.aligned.u32 32;");
    if (tid == 384) {
#pragma unroll
      for (int i = 2; i < NSLOT; i++) mbar_init(full0 + 8 * i, 1);
      asm volatile("fence.mbarrier_init.release.cluster;" ::: "memory");
    }
    __syncwarp();
    asm volatile("barrier.cluster.arrive.relaxed.aligned;" ::: "memory");
    if (warp == 12) {
      SNOW(sa_);
      if (lane == 0) {
#pragma unroll 1
        for (int c = 1; c < 5; c++) {
          if (c == FDELAY_C) { const uint32_t t0 = clk32(); while (clk32() - t0 < FDELAY) {} }
          mbar_expect_tx(full0 + 16 * c, SLOT_BYTES);
          tma2d(sbase + 2 * c * SLOT_BYTES, &P.x[p], c * 64, tg * 192, full0 + 16 * c);
          tma2d(sbase + 2 * c * SLOT_BYTES + 12288, &P.x[p], c * 64, tg * 192 + 96, full0 + 16 * c);
          if (c == 4) break;
          mbar_expect_tx(full0 + 8 + 16 * c, SLOT_BYTES);
          tma3d(sbase + (2 * c + 1) * SLOT_BYTES, &P.wq[p], 0, c * 64, h0 * 3, full0 + 8 + 16 * c);
        }
        asm volatile("prefetch.tensormap [%0];" ::"l"(&P.k[p]) : "memory");
        asm volatile("prefetch.tensormap [%0];" ::"l"(&P.v[p]) : "memory");
        asm volatile("prefetch.tensormap [%0];" ::"l"(&P.wo[p]) : "memory");
      }
      SNOW(sb_);
      __syncwarp();
      asm volatile("barrier.cluster.wait.aligned;" ::: "memory");
      if (lane == 0) {
        TSTAMP(3); CSTAMP(28);
        uint32_t slot = 0, phase = 1;
#pragma unroll 1
        for (int i = NSLOT; i < 49; i++) {
          mbar_wait(empty0 + 8 * slot, phase ^ 1);
          mbar_expect_tx(full0 + 8 * slot, SLOT_BYTES);
          do_item(P, i, p, tg, h0, r, sbase + slot * SLOT_BYTES, full0 + 8 * slot);
          if (++slot == NSLOT) { slot = 0; phase ^= 1; }
        }
        TSTAMP(2); CSTAMP(29);
#pragma unroll 1
        for (int e = 0; e < 23; e++) {
          int j;
          uint32_t bar;
          if (e < 11) {
            slot = (uint32_t)(0x20732087654ull >> (4 * e)) & 15u;
            if (e == 8) mbar_wait(emptye0 + 32, 0);
            else mbar_wait(empty0 + 8 * slot, e >= 5 && e < 8);
            if (e >= 4 && e < 7) {
              mbar_expect_tx(full0 + 8 * slot, SLOT_BYTES);
              do_item(P, 45 + e, p, tg, h0, r, sbase + slot * SLOT_BYTES, full0 + 8 * slot);
              continue;
            }
            j = e < 4 ? 4 * e : e - 6 + (e == 10);
          } else {
            const int n = e - 11;
            slot = oslot(n);
            mbar_wait(emptyo0 + 8 * (n >> 1), 0);
            asm volatile("fence.proxy.async.shared::cta;" ::: "memory");
            j = n + 6 + (n >= 2) + (n >= 5);
          }
          bar = e < 4 ? full0 + FULLE + 8 * e : fullo0 + 8 * (j >> 1);
          mbar_expect_tx(bar, SLOT_BYTES);
          tma2d(sbase + slot * SLOT_BYTES, &P.wo[p], chunk_of(index_at(j >> 1, r, fin), off) * 64, (h0 + HS * (j & 1)) * 192, bar);
        }
        TSTAMP(1); CSTAMP(30);
        if (fin) {
          const uint4* src = g_part + (size_t)(grp * 10 + chunk_of(8 + r, off)) * 7 * (SLOT_BYTES / 16);
#pragma unroll 1
          for (int g = 0; g < (GATHB ? 6 : 4); g++) {
            const uint32_t bar = fullo0 + 8 * (14 + (g >> 2));
            mbar_wait(emptyo0 + 8 * (6 + (g >> 1)), 0);
            asm volatile("fence.proxy.async.shared::cta;" ::: "memory");
            mbar_expect_tx(bar, SLOT_BYTES);
            TSTAMP(4 + g);
            asm volatile("cp.async.bulk.shared::cluster.global.mbarrier::complete_tx::bytes [%0], [%1], %2, [%3];"
                         ::"r"(oslot_addr(sbase, 12 + g)), "l"(src + g * (SLOT_BYTES / 16)), "r"(SLOT_BYTES), "r"(bar) : "memory");
          }
        }
      }
    } else {
      const int w = warp - 13;
      unsigned epoch;
      asm volatile("ld.global.cg.u32 %0, [%1];" : "=r"(epoch) : "l"(P.epoch + grp));
      {
        uint32_t sink = sbase + SINK_OFF + (w * 20 + lane) * 16;
        int un = 0;
        uint32_t rot = 0;
        asm volatile("barrier.cluster.wait.aligned;" ::: "memory");
        mbar_wait(full0 + 8 * PF_TRIG, 0);
        uint32_t due = clk32();
#pragma unroll 1
        for (int ph = PF0 ? -1 : 0; ph < 5; ph++) {
          const char* q;
          int nb = 4, nt = 3, nl = 16;
          uint32_t sb = 589824;
          if (ph == 1 || ph < 0) {
            q = P.wqp[p] + (size_t)(lane * 4 + tg) * 12288 + (h0 + HS * (ph > 0)) * 384 + w * 128;
            nb = 10; nt = 1; sb = 786432;
            if (ph < 0) {
              nl = 20;
              if (lane >= 16) { q = P.xp[p] + (size_t)(tg * 192 + hp * 12 + w * 4 + lane - 16) * 1280; sb = 128; }
              nb = 10 - PF0_FROM; q += PF0_FROM * sb;
            }
          } else {
            q = (ph < 3 ? P.kp[p] : P.vp[p]) + (size_t)(tg * 128 + h0 + HS * (ph == 2 || ph == 4)) * 18432 + (w * 16 + lane) * 128;
          }
#pragma unroll 1
          for (int b = 0; b < nb; b++, q += sb) {
            if (ph > 0 && mbar_test(emptye0 + 32, 0)) break;
#pragma unroll 1
            for (int t = 0; t < nt; t++) {
              if (ph < 0) asm volatile("cp.async.wait_group %0;" ::"n"(PF_WIN0 - 1) : "memory");
              else if (ph < PF_NW) asm volatile("cp.async.wait_group %0;" ::"n"(PF_WIN1 - 1) : "memory");
              else asm volatile("cp.async.wait_group %0;" ::"n"(PF_WIN - 1) : "memory");
              if (PACE) {
                while ((int)(clk32() - due) < 0) __nanosleep(32);
                due += PACE;
              }
              if (!(un & 1)) { PSTAMP(un >> 1); }
              if (lane < nl)
                asm volatile("cp.async.cg.shared.global.L2::128B [%0], [%1], 16;" ::"r"(sink + rot), "l"(q + t * 6144) : "memory");
              asm volatile("cp.async.commit_group;" ::: "memory");
              un++;
              rot = rot == (PF_DEPTH - 1) * 960 ? 0 : rot + 960;
            }
          }
          if (ph == 0) {
            if (lane == 0) {
              asm volatile("st.shared.u32 [%0], %1;" ::"r"(epoch_s), "r"(epoch) : "memory");
              mbar_arrive(eready);
            }
          }
        }
        asm volatile("cp.async.wait_all;" ::: "memory");
      }
    }
    __syncwarp();
    TDUMP();
  } else {
    if (tid == 0) {
      asm volatile("prefetch.tensormap [%0];" ::"l"(&P.x[p]) : "memory");
      asm volatile("prefetch.tensormap [%0];" ::"l"(&P.wq[p]) : "memory");
    }
    {
      const int c = tid & 7, rr = tid >> 3;
      const uint32_t d = sbase + rr * 128 + ((c ^ (rr & 7)) << 4);
      const char* gw = P.wqp[p] + (size_t)(rr & 15) * 12288 + (h0 * 3 + (rr >> 4)) * 128 + c * 16;
      const uint32_t dw = sbase + SLOT_BYTES + (rr >> 4) * 8192 + (rr & 15) * 128 + ((c ^ (rr & 7)) << 4);
      const char* gx = P.xp[p] + (size_t)(tg * 192 + rr) * 1280 + c * 16;
#pragma unroll
      for (int i = 0; i < 4; i++) {
        asm volatile("cp.async.cg.shared.global [%0], [%1], 16;" ::"r"(dw + i * 2048), "l"(gw + i * 196608) : "memory");
        asm volatile("cp.async.cg.shared.global [%0], [%1], 16;" ::"r"(d + i * 6144), "l"(gx + i * 61440) : "memory");
      }
    }
    if (tid == 128) {
      mbar_init(full0, 1); mbar_init(full0 + 8, 1);
      for (int i = 0; i < NSLOT; i++) mbar_init(empty0 + 8 * i, 24);
      for (int i = 0; i < 3; i++) { mbar_init(xfull0 + 8 * i, 1); mbar_init(xempty0 + 8 * i, 4); }
      for (int i = 0; i < 9; i++) mbar_init(emptyo0 + 8 * i, 12);
      mbar_init(eready, 3);
      for (int i = 0; i < 5; i++) mbar_init(emptye0 + 8 * i, 12);
      for (int i = 0; i < 16; i++) mbar_init(fullo0 + 8 * i, (0x2411112221212121ull >> (4 * i)) & 7);
      asm volatile("fence.mbarrier_init.release.cluster;" ::: "memory");
      for (int i = 0; i < 3; i++) mbar_expect_tx(xfull0 + 8 * i, XBUF_BYTES);
      mbar_arrive(full0); mbar_arrive(full0 + 8);
    }
    __syncwarp();
    asm volatile("barrier.cluster.arrive.relaxed.aligned;" ::: "memory");
    asm volatile("setmaxnreg.inc.sync.aligned.u32 160;");
    SNOW(sd_);
    asm volatile("barrier.cluster.wait.aligned;" ::: "memory");
    asm volatile("cp.async.wait_all;" ::: "memory");
    asm volatile("fence.proxy.async.shared::cta;" ::: "memory");
    asm volatile("bar.sync 4, 384;" ::: "memory");
    const int w = warp >> 2;
    const int hf = warp / 3 - w;
    uint32_t o0[48], o1[48];
    const uint32_t never = (out == nullptr);
    {
      Front f{{0, 0}, sbase, full0, mapa(empty0, lane & 1), never, w, lane, hf};
      f.run(o0, o1);
    }
#pragma unroll
    for (int i = 0; i < 12; i++) o0[i] ^= never;
    fence_regs(o0); fence_regs(o1);

    const int wt = tid & 127;
    const int wnext = w == 2 ? 0 : w + 1;
    if (w == 2) asm volatile("bar.arrive 1, 256;" ::: "memory");
    const uint32_t xb = sbase + XBUF_OFF + w * XBUF_BYTES + wt * 16;
    mbar_wait(eready, 0);
    uint32_t tag;
    asm volatile("ld.shared.u32 %0, [%1];" : "=r"(tag) : "r"(epoch_s) : "memory");
    tag = __shfl_sync(0xffffffffu, ~tag & 1u, 0);
    float a[32];
    uint32_t x[16];
    const uint32_t toff = w * XBUF_BYTES + wt * 16;
    uint4* dst;
    auto publish = [&]() {
#pragma unroll
      for (int j = 0; j < 4; j++)
        asm volatile("st.relaxed.gpu.global.v4.b32 [%0], {%1, %2, %3, %4};"
                     ::"l"(dst + j * 128), "r"(x[4 * j]), "r"(x[4 * j + 1]), "r"(x[4 * j + 2]), "r"(x[4 * j + 3]) : "memory");
    };
    auto prepare = [&](int t, bool early) {
      const int k = t >> 1;
      if (early || (index_at(t, r, fin) & 1) != r) {
        if (k == 0) mbar_wait(empty0 + 8 * 8, 1);
        else mbar_wait(xempty0 + 8 * w, (k - 1) & 1);
        if (DEFER && (early ? t != 0 : t == 8)) publish();
        if (early) load_tile(x, oslot_addr(sbase, 2 * t) + toff);
      } else {
        if (DEFER && t == 8) publish();
        const int ci = 2 * k + r, c = chunk_of(ci, off), pos = pos_of(ci, c);
        dst = g_part + (size_t)((grp * 10 + c) * 7 + pos) * (SLOT_BYTES / 16) + w * 512 + wt;
        asm volatile("" : "+l"(dst));
        mbar_wait(xfull0 + 8 * w, k & 1);
        load_tile(x, xb);
        if (k < 4) {
          if (wt == 0) mbar_expect_tx(xfull0 + 8 * w, XBUF_BYTES);
          __syncwarp();
          if (lane == 0) mbar_arrive_cluster(mapa(xempty0 + 8 * w, r ^ 1) + ((x[0] | x[4] | x[8] | x[12]) & never));
        }
      }
      fence_regs(x);
    };
    auto epilogue = [&](int t, bool early) {
      const int ci = index_at(t, r, fin);
      uint32_t z[16];
#pragma unroll
      for (int j = 0; j < 16; j++) z[j] = pack_bf16(a[2 * j], a[2 * j + 1]);
      if (early || (ci & 1) != r) {
        const uint32_t rxb = mapa(xb, r ^ 1);
        const uint32_t rbar = mapa(xfull0 + 8 * w, r ^ 1);
        if (early) {
#pragma unroll
          for (int j = 0; j < 16; j++) z[j] = add_bf16x2(z[j], x[j]);
          fence_regs(z);
        }
        if (lane == 0 && t < 9) mbar_arrive(emptyo0 + 8 * t);
#pragma unroll
        for (int j = 0; j < 4; j++)
          asm volatile("st.async.weak.shared::cluster.mbarrier::complete_tx::bytes.v4.b32 [%0], {%1, %2, %3, %4}, [%5];"
                       ::"r"(rxb + j * 2048), "r"(z[4 * j]), "r"(z[4 * j + 1]), "r"(z[4 * j + 2]), "r"(z[4 * j + 3]), "r"(rbar) : "memory");
      } else {
        if (lane == 0) mbar_arrive(emptyo0 + 8 * t);
#pragma unroll
        for (int j = 0; j < 16; j++) x[j] = add_bf16x2(z[j], x[j]);
#pragma unroll
        for (int j = 0; j < 16; j += 4) x[j] = (x[j] & ~1u) | tag;
        fence_regs(x);
        if (!DEFER || t == 8) publish();
      }
      ESTAMP(20 + t);
    };
    auto finalize = [&]() {
      const int c = chunk_of(8 + r, off);
      TSTAMP(7);
      const uint4* tiles = g_part + (size_t)(grp * 10 + c) * 7 * (SLOT_BYTES / 16) + w * 512 + wt;
      auto load_g = [&](uint32_t (&y)[16], int q) {
#pragma unroll
        for (int j = 0; j < 4; j++)
          asm volatile("ld.relaxed.gpu.global.v4.b32 {%0, %1, %2, %3}, [%4];"
                       : "=r"(y[4 * j]), "=r"(y[4 * j + 1]), "=r"(y[4 * j + 2]), "=r"(y[4 * j + 3])
                       : "l"(tiles + q * (SLOT_BYTES / 16) + j * 128) : "memory");
      };
      const uint32_t tm = tag - 1u;
      const uint32_t t0 = clk32();
      auto settle = [&](uint32_t (&y)[16], int q) {
        while (true) {
          if (tile_ok(y, tm) || clk32() - t0 > SPIN_LIMIT) break;
          load_g(y, q);
        }
        add_tile(a, y);

      };
      mbar_wait(fullo0 + 8 * 14, 0);
      uint32_t ok = 1u;
#pragma unroll
      for (int j = 0; j < 4; j++) {
        uint32_t x[4][4];
#pragma unroll
        for (int q = 0; q < 4; q++)
          asm volatile("ld.shared.v4.b32 {%0, %1, %2, %3}, [%4];"
                       : "=r"(x[q][0]), "=r"(x[q][1]), "=r"(x[q][2]), "=r"(x[q][3]) : "r"(oslot_addr(sbase, 12 + q) + toff + j * 2048) : "memory");
        ok = lop3<0x80>(ok, lop3<0x42>(x[0][0], x[1][0], tm), lop3<0x42>(x[2][0], x[3][0], tm));
#pragma unroll
        for (int i = 0; i < 4; i++) {
          const uint32_t u = add_bf16x2(x[0][i], x[1][i]), v = add_bf16x2(x[2][i], x[3][i]);
          const uint32_t s = add_bf16x2(u, v);
          a[8 * j + 2 * i] = __uint_as_float(s << 16);
          a[8 * j + 2 * i + 1] = __uint_as_float(s & 0xffff0000u);
        }
      }
      if (!ok) {
#pragma unroll
        for (int j = 0; j < 32; j++) a[j] = 0.f;
#pragma unroll 1
        for (int q = 0; q < 4; q++) {
          uint32_t x[16];
          load_g(x, q);
          settle(x, q);
        }
      }
      fence_regs(a);
      TSTAMP(30);
      mbar_wait(fullo0 + 8 * 9, 0);
      asm volatile("bar.sync %0, 256;" ::"r"(1 + w) : "memory");
      wg_fence();
      {
        const uint64_t db = make_desc(oslot_addr(sbase, 18), 16, 1024);
#pragma unroll
        for (int j = 0; j < 12; j++) wgmma_n64_rs_tb(a, o0[4 * j], o0[4 * j + 1], o0[4 * j + 2], o0[4 * j + 3], db + 128 * j, 1);
        wg_commit();
      }
      {
        const uint64_t db = make_desc(oslot_addr(sbase, 19), 16, 1024);
#pragma unroll
        for (int j = 0; j < 12; j++) {
          wgmma_n64_rs_tb(a, o1[4 * j], o1[4 * j + 1], o1[4 * j + 2], o1[4 * j + 3], db + 128 * j, 1);
          if (j == TOKEN_AT && w < 2) asm volatile("bar.arrive %0, 256;" ::"r"(1 + wnext) : "memory");
        }
        wg_commit();
      }
      {
        uint32_t x[16], y0[16], y1[16], y2[16];
        wg_wait<1>();
        load_g(y0, 4); load_g(y1, 5); load_g(y2, 6);
        wg_wait<0>();
        fence_regs(a);
        TSTAMP(19);
        settle(y0, 4); settle(y1, 5); settle(y2, 6);
        fence_regs(a);
        TSTAMP(31);
        mbar_wait(xfull0 + 8 * w, 0); load_tile(x, xb);
        add_tile(a, x);
      }
      TSTAMP(8);
      const int row = tg * 192 + w * 64 + (wt >> 5) * 16 + ((wt >> 2) & 7);
      uint4* d0 = reinterpret_cast<uint4*>(out + (size_t)row * 1280 + p * 640 + c * 64 + (wt & 3) * 8);
      const bool b0 = wt & 1, b1 = wt & 2;
      __syncwarp();
#pragma unroll
      for (int u = 0; u < 4; u++) {
        uint32_t x[4];
#pragma unroll
        for (int i = 0; i < 4; i++) {
          const int j = (u & 1) * 4 + i;
          x[i] = pack_bf16(a[4 * j + (u >> 1) * 2], a[4 * j + (u >> 1) * 2 + 1]);
        }
        uint32_t v;
        v = __shfl_xor_sync(0xffffffffu, b0 ? x[0] : x[1], 1); if (b0) x[0] = v; else x[1] = v;
        v = __shfl_xor_sync(0xffffffffu, b0 ? x[2] : x[3], 1); if (b0) x[2] = v; else x[3] = v;
        v = __shfl_xor_sync(0xffffffffu, b1 ? x[0] : x[2], 2); if (b1) x[0] = v; else x[2] = v;
        v = __shfl_xor_sync(0xffffffffu, b1 ? x[1] : x[3], 2); if (b1) x[1] = v; else x[3] = v;
        d0[(u & 1) * 4 + (u >> 1) * 8 * 160] = make_uint4(x[0], x[1], x[2], x[3]);
      }
      if (hp == 1 && tid == 0) asm volatile("red.relaxed.gpu.global.add.u32 [%0], 1;" ::"l"(P.epoch + grp) : "memory");
    };
#pragma unroll 1
    for (int t = 0; t < 10; t++) {
      if (t < 8 && !(t & 1)) {
        oproj_chunk<true>(a, o0, o1, t, sbase, fullo0, w, wnext, true, [&]() { prepare(t, true); });
        TSTAMP(10 + t);
        epilogue(t, true);
        t++;
      }
      if (t == 9 && fin) { finalize(); break; }
      oproj_chunk<false>(a, o0, o1, t, sbase, fullo0, w, wnext, t < 9 || w < 2, [&]() { prepare(t, false); });
      TSTAMP(10 + t);
      epilogue(t, false);
    }
    TSTAMP(9);
    __syncwarp();
    TDUMP();
  }
}

typedef CUresult (*EncodeFn)(CUtensorMap*, CUtensorMapDataType, cuuint32_t, void*, const cuuint64_t*, const cuuint64_t*,
                             const cuuint32_t*, const cuuint32_t*, CUtensorMapInterleave, CUtensorMapSwizzle,
                             CUtensorMapL2promotion, CUtensorMapFloatOOBfill);

static void encode(EncodeFn fn, CUtensorMap* m, const void* ptr, int rank, const cuuint64_t* dims, const cuuint64_t* strides,
                   const cuuint32_t* box) {
  cuuint32_t es[5] = {1, 1, 1, 1, 1};
  fn(m, CU_TENSOR_MAP_DATA_TYPE_BFLOAT16, (cuuint32_t)rank, const_cast<void*>(ptr), dims, strides, box, es,
     CU_TENSOR_MAP_INTERLEAVE_NONE, CU_TENSOR_MAP_SWIZZLE_128B, CU_TENSOR_MAP_L2_PROMOTION_L2_256B,
     CU_TENSOR_MAP_FLOAT_OOB_FILL_NONE);
}

}

extern "C" void kernel_launch(void* const* d_in, const int* in_sizes, int n_in, void* d_out, int out_size) {
  using namespace fk;
  static Params params;
  static const void* cached[10] = {nullptr};
  static EncodeFn fn = nullptr;
  if (!fn) {
    void* f = nullptr;
    cudaDriverEntryPointQueryResult st;
    cudaGetDriverEntryPoint("cuTensorMapEncodeTiled", &f, cudaEnableDefault, &st);
    fn = (EncodeFn)f;
    void* e = nullptr;
    cudaGetSymbolAddress(&e, g_epoch);
    params.epoch = (unsigned int*)e;
    cudaFuncSetAttribute(fused_kernel, cudaFuncAttributeMaxDynamicSharedMemorySize, SMEM_BYTES);
  }
  bool same = true;
  for (int i = 0; i < 10; i++) same = same && (cached[i] == d_in[i]);
  if (!same) {
    for (int p = 0; p < 2; p++) {
      const void* x = d_in[5 * p + 0];
      const void* k = d_in[5 * p + 1];
      const void* v = d_in[5 * p + 2];
      const void* wq = d_in[5 * p + 3];
      const void* wo = d_in[5 * p + 4];
      params.kp[p] = (const char*)k; params.vp[p] = (const char*)v;
      params.wqp[p] = (const char*)wq; params.xp[p] = (const char*)x;
      {
        cuuint64_t d[2] = {640, 768}, s[1] = {1280};
        cuuint32_t b[2] = {64, 96};
        encode(fn, &params.x[p], x, 2, d, s, b);
      }
      {
        cuuint64_t d[3] = {64, 640, 96}, s[2] = {12288, 128};
        cuuint32_t b[3] = {64, 64, 3};
        encode(fn, &params.wq[p], wq, 3, d, s, b);
      }
      {
        cuuint64_t d[4] = {192, 48, 32, 16}, s[3] = {384, 18432, 589824};
        cuuint32_t b[4] = {64, 48, 1, 4};
        encode(fn, &params.k[p], k, 4, d, s, b);
        encode(fn, &params.v[p], v, 4, d, s, b);
      }
      {
        cuuint64_t d[2] = {640, 6144}, s[1] = {1280};
        cuuint32_t b[2] = {64, 192};
        encode(fn, &params.wo[p], wo, 2, d, s, b);
      }
    }
    for (int i = 0; i < 10; i++) cached[i] = d_in[i];
  }
  fused_kernel<<<128, NTHREADS, SMEM_BYTES>>>(params, (__nv_bfloat16*)d_out);
}
```

```cpp
#include <cuda_runtime.h>
#include <cuda_bf16.h>
#include <cuda.h>
#include <stdint.h>

#define PF_ON 1
#define PF_WIN 4
#define PF_WIN1 4
#define PF_WIN0 3
#define FDELAY 500
#define FDELAY_C 1
#define GATHB 0
#define DEFER 0
#define PRE3 1
#define YFIRST 1
#define PACE 485
#define PF_TRIG 3
#define PF0_FROM 5
#define PF_NW 2
#define PF0 1
#define QMMA 4
#define TOKEN_AT 8
#define TOKEN_S 8
#define WOPF 6
#define WOPF0 -2
#define WOPACE 485
#define STAG 1
#define TOK0 0x3eaabu
#define TOK1 0x57ffdu
#define TOK2 0xa555au
#define FIRSTW 2
#define SPIN_LIMIT (1u << 27)

namespace fk {

#define HEADMAP 0
constexpr int HM = HEADMAP ? 1 : 2, HS = HEADMAP ? 16 : 1;
constexpr int SLOT_BYTES = 24576;
constexpr int NSLOT = 9;
constexpr int XBUF_BYTES = 8192;
constexpr int XBUF_OFF = 8 * SLOT_BYTES;
constexpr int BAR_OFF = NSLOT * SLOT_BYTES;
constexpr int FULLO = 192, FULLE = 272, EMPTYE = 360;
constexpr int SINK_OFF = BAR_OFF + 1024;
constexpr int PF_DEPTH = 9;
constexpr int SMEM_BYTES = SINK_OFF + PF_DEPTH * 960 + 1024;
constexpr int NTHREADS = 512;

struct Params {
  CUtensorMap x[2], wq[2], k[2], v[2], wo[2];
  const char* kp[2]; const char* vp[2]; const char* wqp[2]; const char* xp[2]; const char* wop[2];
  unsigned int* epoch;
};

__device__ uint4 g_part[8 * 10 * 7 * (SLOT_BYTES / 16)];
__device__ unsigned int g_epoch[8];
#define TSTAMP(i)
#define PSTAMP(i)
#define HSTAMP(i)
#define GSTAMP(a, b)
#define HSTAMP2(i)
#define CSTAMP(i)
#define TDUMP()

#define XSTAMP(i)
#define ESTAMP(i) TSTAMP(i)
#define QSTAMP(i)
#define RSTAMP(i)
#define OSTAMP(i)
#define ZSTAMP(i) TSTAMP(i)
#define FSTAMP(i)
#define SNOW(v)
#define SPUT(i, v)
__device__ __forceinline__ uint32_t smem_u32(const void* p) { return (uint32_t)__cvta_generic_to_shared(p); }
__device__ __forceinline__ void mbar_init(uint32_t bar, uint32_t cnt) {
  asm volatile("mbarrier.init.shared::cta.b64 [%0], %1;" ::"r"(bar), "r"(cnt) : "memory");
}
__device__ __forceinline__ void mbar_expect_tx(uint32_t bar, uint32_t bytes) {
  asm volatile("mbarrier.arrive.expect_tx.shared::cta.b64 _, [%0], %1;" ::"r"(bar), "r"(bytes) : "memory");
}
__device__ __forceinline__ uint32_t mapa(uint32_t addr, uint32_t cta) {
  uint32_t r;
  asm volatile("mapa.shared::cluster.u32 %0, %1, %2;" : "=r"(r) : "r"(addr), "r"(cta));
  return r;
}
__device__ __forceinline__ void mbar_arrive_cluster(uint32_t remote_bar) {
  asm volatile("mbarrier.arrive.shared::cluster.b64 _, [%0];" ::"r"(remote_bar) : "memory");
}
__device__ __forceinline__ uint32_t mbar_try(uint32_t bar, uint32_t parity) {
  uint32_t ok;
  asm volatile("{\n.reg .pred p;\nmbarrier.try_wait.parity.shared::cta.b64 p, [%1], %2;\nselp.u32 %0, 1, 0, p;\n}\n"
               : "=r"(ok) : "r"(bar), "r"(parity) : "memory");
  return ok;
}
__device__ __forceinline__ uint32_t mbar_test(uint32_t bar, uint32_t parity) {
  uint32_t ok;
  asm volatile("{\n.reg .pred p;\nmbarrier.test_wait.parity.shared::cta.b64 p, [%1], %2;\nselp.u32 %0, 1, 0, p;\n}\n"
               : "=r"(ok) : "r"(bar), "r"(parity) : "memory");
  return ok;
}
__device__ __forceinline__ uint32_t mbar_try_cluster(uint32_t bar, uint32_t parity) {
  uint32_t ok;
  asm volatile("{\n.reg .pred p;\nmbarrier.try_wait.parity.acquire.cluster.shared::cta.b64 p, [%1], %2;\nselp.u32 %0, 1, 0, p;\n}\n"
               : "=r"(ok) : "r"(bar), "r"(parity) : "memory");
  return ok;
}
__device__ __forceinline__ uint32_t clk32() {
  uint32_t t;
  asm volatile("mov.u32 %0, %%clock;" : "=r"(t));
  return t;
}
#define DBGREC(a, b)
__device__ __forceinline__ void mbar_wait(uint32_t bar, uint32_t parity) {
  if (mbar_try(bar, parity)) return;
  const uint32_t t0 = clk32();
  while (!mbar_try(bar, parity)) {
    if (clk32() - t0 > SPIN_LIMIT) { DBGREC(bar, parity); break; }
  }
}
__device__ __forceinline__ void mbar_wait_cluster(uint32_t bar, uint32_t parity) {
  if (mbar_try_cluster(bar, parity)) return;
  const uint32_t t0 = clk32();
  while (!mbar_try_cluster(bar, parity)) {
    if (clk32() - t0 > SPIN_LIMIT) break;
  }
}
__device__ __forceinline__ void cluster_sync() {
  asm volatile("barrier.cluster.arrive.release.aligned;\nbarrier.cluster.wait.acquire.aligned;\n" ::: "memory");
}
__device__ __forceinline__ void tma2d(uint32_t dst, const CUtensorMap* m, int c0, int c1, uint32_t bar) {
  asm volatile("cp.async.bulk.tensor.2d.shared::cluster.global.mbarrier::complete_tx::bytes [%0], [%1, {%3, %4}], [%2];"
               ::"r"(dst), "l"(m), "r"(bar), "r"(c0), "r"(c1) : "memory");
}
__device__ __forceinline__ void tma2d_mc(uint32_t dst, const CUtensorMap* m, int c0, int c1, uint32_t bar, uint16_t mask) {
  asm volatile("cp.async.bulk.tensor.2d.shared::cluster.global.mbarrier::complete_tx::bytes.multicast::cluster [%0], [%1, {%3, %4}], [%2], %5;"
               ::"r"(dst), "l"(m), "r"(bar), "r"(c0), "r"(c1), "h"(mask) : "memory");
}
__device__ __forceinline__ void tma3d(uint32_t dst, const CUtensorMap* m, int c0, int c1, int c2, uint32_t bar) {
  asm volatile("cp.async.bulk.tensor.3d.shared::cluster.global.mbarrier::complete_tx::bytes [%0], [%1, {%3, %4, %5}], [%2];"
               ::"r"(dst), "l"(m), "r"(bar), "r"(c0), "r"(c1), "r"(c2) : "memory");
}
__device__ __forceinline__ void tma4d(uint32_t dst, const CUtensorMap* m, int c0, int c1, int c2, int c3, uint32_t bar) {
  asm volatile("cp.async.bulk.tensor.4d.shared::cluster.global.mbarrier::complete_tx::bytes [%0], [%1, {%3, %4, %5, %6}], [%2];"
               ::"r"(dst), "l"(m), "r"(bar), "r"(c0), "r"(c1), "r"(c2), "r"(c3) : "memory");
}
__device__ __forceinline__ void mbar_arrive(uint32_t bar) {
  asm volatile("mbarrier.arrive.shared::cta.b64 _, [%0];" ::"r"(bar) : "memory");
}
__device__ __forceinline__ uint32_t touch_l2(const void* p) {
  uint32_t v;
  asm volatile("ld.global.cg.L2::128B.b32 %0, [%1];" : "=r"(v) : "l"(p));
  return v;
}
__device__ __forceinline__ unsigned ld_acquire(const unsigned* p) {
  unsigned v;
  asm volatile("ld.acquire.gpu.global.u32 %0, [%1];" : "=r"(v) : "l"(p) : "memory");
  return v;
}
__device__ __forceinline__ void wg_fence() { asm volatile("wgmma.fence.sync.aligned;" ::: "memory"); }
__device__ __forceinline__ void wg_commit() { asm volatile("wgmma.commit_group.sync.aligned;" ::: "memory"); }
template <int N> __device__ __forceinline__ void wg_wait() { asm volatile("wgmma.wait_group.sync.aligned %0;" ::"n"(N) : "memory"); }
template <int N> __device__ __forceinline__ void fence_regs(float (&d)[N]) {
#pragma unroll
  for (int i = 0; i < N; i++) asm volatile("" : "+f"(d[i])::"memory");
}
template <int N> __device__ __forceinline__ void fence_regs(uint32_t (&d)[N]) {
#pragma unroll
  for (int i = 0; i < N; i++) asm volatile("" : "+r"(d[i])::"memory");
}
template <int N> __device__ __forceinline__ void pin_regs(const uint32_t* d, uint32_t never, uint32_t addr) {
#pragma unroll
  for (int i = 0; i < N; i += 4)
    asm volatile("{\n.reg .pred p;\nsetp.ne.u32 p, %5, 0;\n@p st.shared.v4.b32 [%0], {%1, %2, %3, %4};\n}\n"
                 ::"r"(addr), "r"(d[i]), "r"(d[i + 1]), "r"(d[i + 2]), "r"(d[i + 3]), "r"(never) : "memory");
}
__device__ __forceinline__ uint32_t pack_bf16(float lo, float hi) {
  uint32_t r;
  asm("cvt.rn.bf16x2.f32 %0, %1, %2;" : "=r"(r) : "f"(hi), "f"(lo));
  return r;
}
__device__ __forceinline__ float ex2(float x) {
  float r;
  asm("ex2.approx.ftz.f32 %0, %1;" : "=f"(r) : "f"(x));
  return r;
}
__device__ __forceinline__ float rcp(float x) {
  float r;
  asm("rcp.approx.ftz.f32 %0, %1;" : "=f"(r) : "f"(x));
  return r;
}
__device__ __forceinline__ uint64_t make_desc(uint32_t addr, uint32_t lbo, uint32_t sbo) {
  return (uint64_t)((addr & 0x3FFFFu) >> 4) | ((uint64_t)(lbo >> 4) << 16) | ((uint64_t)(sbo >> 4) << 32) | (1ull << 62);
}

__device__ __forceinline__ void wgmma_n192_ss_tb(float (&d)[96], uint64_t da, uint64_t db, int scale_d) {
  asm volatile("{\n.reg .pred p;\nsetp.ne.b32 p, %98, 0;\n"
    "wgmma.mma_async.sync.aligned.m64n192k16.f32.bf16.bf16 "
    "{%0, %1, %2, %3, %4, %5, %6, %7, %8, %9, %10, %11, %12, %13, %14, %15, %16, %17, %18, %19, %20, %21, %22, %23, %24, %25, %26, %27, %28, %29, %30, %31, %32, %33, %34, %35, %36, %37, %38, %39, %40, %41, %42, %43, %44, %45, %46, %47, %48, %49, %50, %51, %52, %53, %54, %55, %56, %57, %58, %59, %60, %61, %62, %63, %64, %65, %66, %67, %68, %69, %70, %71, %72, %73, %74, %75, %76, %77, %78, %79, %80, %81, %82, %83, %84, %85, %86, %87, %88, %89, %90, %91, %92, %93, %94, %95}, "
    "%96, %97, p, 1, 1, 0, 1;\n}\n"
    : "+f"(d[0]), "+f"(d[1]), "+f"(d[2]), "+f"(d[3]), "+f"(d[4]), "+f"(d[5]), "+f"(d[6]), "+f"(d[7]), "+f"(d[8]), "+f"(d[9]), "+f"(d[10]), "+f"(d[11]), "+f"(d[12]), "+f"(d[13]), "+f"(d[14]), "+f"(d[15]), "+f"(d[16]), "+f"(d[17]), "+f"(d[18]), "+f"(d[19]), "+f"(d[20]), "+f"(d[21]), "+f"(d[22]), "+f"(d[23]), "+f"(d[24]), "+f"(d[25]), "+f"(d[26]), "+f"(d[27]), "+f"(d[28]), "+f"(d[29]), "+f"(d[30]), "+f"(d[31]), "+f"(d[32]), "+f"(d[33]), "+f"(d[34]), "+f"(d[35]), "+f"(d[36]), "+f"(d[37]), "+f"(d[38]), "+f"(d[39]), "+f"(d[40]), "+f"(d[41]), "+f"(d[42]), "+f"(d[43]), "+f"(d[44]), "+f"(d[45]), "+f"(d[46]), "+f"(d[47]), "+f"(d[48]), "+f"(d[49]), "+f"(d[50]), "+f"(d[51]), "+f"(d[52]), "+f"(d[53]), "+f"(d[54]), "+f"(d[55]), "+f"(d[56]), "+f"(d[57]), "+f"(d[58]), "+f"(d[59]), "+f"(d[60]), "+f"(d[61]), "+f"(d[62]), "+f"(d[63]), "+f"(d[64]), "+f"(d[65]), "+f"(d[66]), "+f"(d[67]), "+f"(d[68]), "+f"(d[69]), "+f"(d[70]), "+f"(d[71]), "+f"(d[72]), "+f"(d[73]), "+f"(d[74]), "+f"(d[75]), "+f"(d[76]), "+f"(d[77]), "+f"(d[78]), "+f"(d[79]), "+f"(d[80]), "+f"(d[81]), "+f"(d[82]), "+f"(d[83]), "+f"(d[84]), "+f"(d[85]), "+f"(d[86]), "+f"(d[87]), "+f"(d[88]), "+f"(d[89]), "+f"(d[90]), "+f"(d[91]), "+f"(d[92]), "+f"(d[93]), "+f"(d[94]), "+f"(d[95])
    : "l"(da), "l"(db), "r"(scale_d));
}
__device__ __forceinline__ void wgmma_n96_rs(float (&d)[48], uint32_t a0, uint32_t a1, uint32_t a2, uint32_t a3, uint64_t db, int scale_d) {
  asm volatile("{\n.reg .pred p;\nsetp.ne.b32 p, %53, 0;\n"
    "wgmma.mma_async.sync.aligned.m64n96k16.f32.bf16.bf16 "
    "{%0, %1, %2, %3, %4, %5, %6, %7, %8, %9, %10, %11, %12, %13, %14, %15, %16, %17, %18, %19, %20, %21, %22, %23, %24, %25, %26, %27, %28, %29, %30, %31, %32, %33, %34, %35, %36, %37, %38, %39, %40, %41, %42, %43, %44, %45, %46, %47}, "
    "{%48, %49, %50, %51}, %52, p, 1, 1, 0;\n}\n"
    : "+f"(d[0]), "+f"(d[1]), "+f"(d[2]), "+f"(d[3]), "+f"(d[4]), "+f"(d[5]), "+f"(d[6]), "+f"(d[7]), "+f"(d[8]), "+f"(d[9]), "+f"(d[10]), "+f"(d[11]), "+f"(d[12]), "+f"(d[13]), "+f"(d[14]), "+f"(d[15]), "+f"(d[16]), "+f"(d[17]), "+f"(d[18]), "+f"(d[19]), "+f"(d[20]), "+f"(d[21]), "+f"(d[22]), "+f"(d[23]), "+f"(d[24]), "+f"(d[25]), "+f"(d[26]), "+f"(d[27]), "+f"(d[28]), "+f"(d[29]), "+f"(d[30]), "+f"(d[31]), "+f"(d[32]), "+f"(d[33]), "+f"(d[34]), "+f"(d[35]), "+f"(d[36]), "+f"(d[37]), "+f"(d[38]), "+f"(d[39]), "+f"(d[40]), "+f"(d[41]), "+f"(d[42]), "+f"(d[43]), "+f"(d[44]), "+f"(d[45]), "+f"(d[46]), "+f"(d[47])
    : "r"(a0), "r"(a1), "r"(a2), "r"(a3), "l"(db), "r"(scale_d));
}
__device__ __forceinline__ void wgmma_n64_rs_tb(float (&d)[32], uint32_t a0, uint32_t a1, uint32_t a2, uint32_t a3, uint64_t db, int scale_d) {
  asm volatile("{\n.reg .pred p;\nsetp.ne.b32 p, %37, 0;\n"
    "wgmma.mma_async.sync.aligned.m64n64k16.f32.bf16.bf16 "
    "{%0, %1, %2, %3, %4, %5, %6, %7, %8, %9, %10, %11, %12, %13, %14, %15, %16, %17, %18, %19, %20, %21, %22, %23, %24, %25, %26, %27, %28, %29, %30, %31}, "
    "{%32, %33, %34, %35}, %36, p, 1, 1, 1;\n}\n"
    : "+f"(d[0]), "+f"(d[1]), "+f"(d[2]), "+f"(d[3]), "+f"(d[4]), "+f"(d[5]), "+f"(d[6]), "+f"(d[7]), "+f"(d[8]), "+f"(d[9]), "+f"(d[10]), "+f"(d[11]), "+f"(d[12]), "+f"(d[13]), "+f"(d[14]), "+f"(d[15]), "+f"(d[16]), "+f"(d[17]), "+f"(d[18]), "+f"(d[19]), "+f"(d[20]), "+f"(d[21]), "+f"(d[22]), "+f"(d[23]), "+f"(d[24]), "+f"(d[25]), "+f"(d[26]), "+f"(d[27]), "+f"(d[28]), "+f"(d[29]), "+f"(d[30]), "+f"(d[31])
    : "r"(a0), "r"(a1), "r"(a2), "r"(a3), "l"(db), "r"(scale_d));
}

__device__ __forceinline__ int chunk_of(int i, int off) { const int c = i + off; return c >= 10 ? c - 10 : c; }
__device__ __forceinline__ int pos_of(int i, int c) { return i - (i > chunk_of(c, 6)) - (i > chunk_of(c, 1)); }
__device__ __forceinline__ int index_at(int t, int r, bool fin) { return (r == 0 && (t < 8 || fin)) ? (t ^ 1) : t; }

constexpr int KPOS = 43;
__device__ __forceinline__ void do_item(const Params& P, int i, int p, int tg, int h0, int r, uint32_t dst, uint32_t bar) {
  if (i >= 46) {
    const int h1 = i >= 49;
    tma4d(dst, &P.v[p], (i - 46 - 3 * h1) * 64, 0, h0 + HS * h1, tg * 4, bar);
  } else if (i >= KPOS && i < KPOS + 3) {
    tma4d(dst, &P.k[p], (i - KPOS) * 64, 0, h0 + HS, tg * 4, bar);
  } else if (i >= 20 && i < 23) {
    tma4d(dst, &P.k[p], (i - 20) * 64, 0, h0, tg * 4, bar);
  } else {
    const int hh = i >= 23;
    const int j = i - 23 * hh - 3 * (i >= KPOS);
    const int kc = j >> 1;
    if (!(j & 1)) tma2d_mc(dst + r * 12288, &P.x[p], kc * 64, tg * 192 + r * 96, bar, (uint16_t)3);
    else tma3d(dst, &P.wq[p], 0, kc * 64, (h0 + HS * hh) * 3, bar);
  }
}

struct Ring {
  uint32_t slot, phase;
  __device__ __forceinline__ void advance() {
    if (++slot == NSLOT) { slot = 0; phase ^= 1; }
  }
};

__device__ __forceinline__ void load_tile(uint32_t (&x)[16], uint32_t addr) {
#pragma unroll
  for (int j = 0; j < 4; j++)
    asm volatile("ld.shared.v4.b32 {%0, %1, %2, %3}, [%4];"
                 : "=r"(x[4 * j]), "=r"(x[4 * j + 1]), "=r"(x[4 * j + 2]), "=r"(x[4 * j + 3]) : "r"(addr + j * 2048) : "memory");
}
__device__ __forceinline__ void store_tile(uint32_t addr, const float (&a)[32]) {
#pragma unroll
  for (int j = 0; j < 4; j++)
    asm volatile("st.shared.v4.b32 [%0], {%1, %2, %3, %4};"
                 ::"r"(addr + j * 2048), "r"(pack_bf16(a[8 * j], a[8 * j + 1])), "r"(pack_bf16(a[8 * j + 2], a[8 * j + 3])),
                   "r"(pack_bf16(a[8 * j + 4], a[8 * j + 5])), "r"(pack_bf16(a[8 * j + 6], a[8 * j + 7])) : "memory");
}
__device__ __forceinline__ uint32_t add_bf16x2(uint32_t a, uint32_t b) {
  uint32_t r;
  asm("add.rn.bf16x2 %0, %1, %2;" : "=r"(r) : "r"(a), "r"(b));
  return r;
}
template <int LUT> __device__ __forceinline__ uint32_t lop3(uint32_t a, uint32_t b, uint32_t c) {
  uint32_t r;
  asm("lop3.b32 %0, %1, %2, %3, %4;" : "=r"(r) : "r"(a), "r"(b), "r"(c), "n"(LUT));
  return r;
}
__device__ __forceinline__ uint32_t tile_ok(const uint32_t (&y)[16], uint32_t tm) {
  return (y[0] ^ tm) & (y[4] ^ tm) & (y[8] ^ tm) & (y[12] ^ tm) & 1u;
}
__device__ __forceinline__ void add_tile(float (&a)[32], const uint32_t (&x)[16]) {
#pragma unroll
  for (int j = 0; j < 16; j++) {
    a[2 * j] += __uint_as_float(x[j] << 16);
    a[2 * j + 1] += __uint_as_float(x[j] & 0xffff0000u);
  }
}
constexpr uint64_t OSLOTS = 0x83d65683d6541d9ull;
__device__ __forceinline__ uint32_t oslot(uint32_t j) { return (uint32_t)(OSLOTS >> (3 * j)) & 7u; }

struct Front {
  Ring rg;
  uint32_t sbase, full0, rel0, never;
  int w, lane, hf;
  __device__ __forceinline__ uint32_t tsb() const { return full0 + 512 + w * 128; }
  __device__ __forceinline__ void release(uint32_t s) const { if (lane < 2) mbar_arrive_cluster(rel0 + 8 * s); }
  __device__ __forceinline__ uint32_t next() {
    const uint32_t s = rg.slot;
    mbar_wait(full0 + 8 * s, rg.phase);
    rg.advance();
    return s;
  }
  template <bool FIRST> __device__ __forceinline__ void qchunk(float (&acc)[96], uint32_t& sx, uint32_t& sw) {
    sx = next(); sw = next();
    const uint64_t da = make_desc(sbase + sx * SLOT_BYTES + w * 8192, 16, 1024);
    const uint64_t db = make_desc(sbase + sw * SLOT_BYTES, 8192, 1024);
    wg_fence();
#pragma unroll
    for (int s = 0; s < QMMA; s++) wgmma_n192_ss_tb(acc, da + 2 * s, db + 128 * s, !FIRST || s != 0);
    wg_commit();
  }
  __device__ __forceinline__ void qrest(float (&acc)[96], uint32_t (&qf)[48], uint32_t psx, uint32_t psw, int kc0, int tbase) {
#pragma unroll 1
    for (int kc = kc0; kc < 10; kc++) {
      uint32_t sx, sw;
      qchunk<false>(acc, sx, sw);
      QSTAMP(20 + kc);
      wg_wait<1>(); release(psx); release(psw);
      psx = sx; psw = sw;
    }
    wg_wait<0>();
    fence_regs(acc);
    release(psx); release(psw);
#pragma unroll
    for (int i = 24; i < 48; i++) qf[i] = pack_bf16(acc[2 * i], acc[2 * i + 1]);
    pin_regs<24>(qf + 24, never, full0);
#pragma unroll
    for (int i = 0; i < 24; i++) qf[i] = pack_bf16(acc[2 * i], acc[2 * i + 1]);
    pin_regs<24>(qf, never, full0);
    fence_regs(qf);
  }
  __device__ __forceinline__ void scores(float (&v)[24], const uint32_t (&qf)[48]) {
    float sacc[48];
    uint32_t ks[3];
#pragma unroll
    for (int dc = 0; dc < 3; dc++) {
      ks[dc] = next();
      const uint64_t db = make_desc(sbase + ks[dc] * SLOT_BYTES + w * 6144, 16, 1024);
      wg_fence();
#pragma unroll
      for (int s = 0; s < 4; s++) {
        const int j = dc * 4 + s;
        wgmma_n96_rs(sacc, qf[4 * j], qf[4 * j + 1], qf[4 * j + 2], qf[4 * j + 3], db + 2 * s, j != 0);
      }
    }
    wg_commit();
    wg_wait<0>();
    fence_regs(sacc);
    release(ks[0]); release(ks[1]); release(ks[2]);
#pragma unroll
    for (int i = 0; i < 24; i++) v[i] = hf ? sacc[24 + i] : sacc[i];
    fence_regs(v);
  }
  __device__ __forceinline__ void softmax(uint32_t (&pk)[12], float (&v)[24]) {
    float m0 = v[0], m1 = v[2];
#pragma unroll
    for (int t = 0; t < 6; t++) {
      m0 = fmaxf(m0, fmaxf(v[4 * t], v[4 * t + 1]));
      m1 = fmaxf(m1, fmaxf(v[4 * t + 2], v[4 * t + 3]));
    }
    m0 = fmaxf(m0, __shfl_xor_sync(0xffffffffu, m0, 1));
    m1 = fmaxf(m1, __shfl_xor_sync(0xffffffffu, m1, 1));
    m0 = fmaxf(m0, __shfl_xor_sync(0xffffffffu, m0, 2));
    m1 = fmaxf(m1, __shfl_xor_sync(0xffffffffu, m1, 2));
    const float cs = 0.07216878364870322f * 1.4426950408889634f;
    const float b0 = m0 * cs, b1 = m1 * cs;
    float s0 = 0.f, s1 = 0.f;
#pragma unroll
    for (int t = 0; t < 6; t++) {
      v[4 * t] = ex2(fmaf(v[4 * t], cs, -b0));
      v[4 * t + 1] = ex2(fmaf(v[4 * t + 1], cs, -b0));
      v[4 * t + 2] = ex2(fmaf(v[4 * t + 2], cs, -b1));
      v[4 * t + 3] = ex2(fmaf(v[4 * t + 3], cs, -b1));
      s0 += v[4 * t] + v[4 * t + 1];
      s1 += v[4 * t + 2] + v[4 * t + 3];
    }
    s0 += __shfl_xor_sync(0xffffffffu, s0, 1);
    s1 += __shfl_xor_sync(0xffffffffu, s1, 1);
    s0 += __shfl_xor_sync(0xffffffffu, s0, 2);
    s1 += __shfl_xor_sync(0xffffffffu, s1, 2);
    const float r0 = rcp(s0), r1 = rcp(s1);
#pragma unroll
    for (int t = 0; t < 6; t++) {
      pk[2 * t] = pack_bf16(v[4 * t] * r0, v[4 * t + 1] * r0);
      pk[2 * t + 1] = pack_bf16(v[4 * t + 2] * r1, v[4 * t + 3] * r1);
    }
    pin_regs<12>(pk, never, full0);
    fence_regs(pk);
  }
  __device__ __forceinline__ void expand(uint32_t (&pa)[24], uint32_t (&pk)[12]) {
    fence_regs(pk);
#pragma unroll
    for (int i = 0; i < 12; i++) {
      pa[i] = hf ? 0u : pk[i];
      pa[12 + i] = hf ? pk[i] : 0u;
    }
    fence_regs(pa);
  }
  __device__ __forceinline__ void pv(float (&oa)[32], const uint32_t (&pa)[24], int s, int parity) {
    mbar_wait(full0 + 8 * s, parity);
    const uint64_t db = make_desc(sbase + s * SLOT_BYTES + w * 6144, 16, 1024);
    wg_fence();
#pragma unroll
    for (int j = 0; j < 6; j++) wgmma_n64_rs_tb(oa, pa[4 * j], pa[4 * j + 1], pa[4 * j + 2], pa[4 * j + 3], db + 128 * j, j != 0);
  }
  __device__ __forceinline__ void pack16(uint32_t* o, const float (&oa)[32]) {
#pragma unroll
    for (int i = 0; i < 16; i++) o[i] = pack_bf16(oa[2 * i], oa[2 * i + 1]);
    pin_regs<16>(o, never, full0);
  }
  __device__ __forceinline__ void early(float (&a)[32], const uint32_t (&o0)[48], int t) {
    mbar_wait(full0 + FULLE + 8 * t, 0);
    const uint64_t db = make_desc(sbase + (4 + t) * SLOT_BYTES, 16, 1024);
    wg_fence();
#pragma unroll
    for (int j = 0; j < 12; j++)
      wgmma_n64_rs_tb(a, o0[4 * j], o0[4 * j + 1], o0[4 * j + 2], o0[4 * j + 3], db + 128 * j, j != 0);
    wg_commit();
  }
  __device__ __forceinline__ void park(float (&a)[32], int t) {
    fence_regs(a);
    if (lane == 0) mbar_arrive(full0 + EMPTYE + 8 * (t + 1));
    mbar_wait(full0 + EMPTYE + 8 * t, 0);
    uint32_t tid;
    asm volatile("mov.u32 %0, %%tid.x;" : "=r"(tid));
    store_tile(sbase + oslot(4 * t) * SLOT_BYTES + (tid >> 7) * XBUF_BYTES + (tid & 127) * 16, a);
  }
  __device__ __forceinline__ void run(uint32_t (&o0)[48], uint32_t (&o1)[48]) {
    uint32_t pk[12], pa[24];
    float v[24];
    {
      uint32_t qf[48];
      {
        float acc[96];
        uint32_t sx, sw;
        qchunk<true>(acc, sx, sw);
        { const int tbase = 1; (void)tbase; QSTAMP(20); }
        qrest(acc, qf, sx, sw, 1, 1);
      }
      TSTAMP(1);
      scores(v, qf);
      TSTAMP(2);
    }
    {
      uint32_t qf[48];
      {
        float acc[96];
        uint32_t ax, aw, bx, bw;
        qchunk<true>(acc, ax, aw);
        qchunk<false>(acc, bx, bw);
        softmax(pk, v);
        TSTAMP(3);
        wg_wait<1>(); release(ax); release(aw);
        qrest(acc, qf, bx, bw, 2, 4);
      }
      TSTAMP(4);
      scores(v, qf);
      TSTAMP(5);
    }
    {
      float oa[32], ob[32], oc[32];
      expand(pa, pk);
      pv(oa, pa, 1, 1); pv(ob, pa, 2, 1); pv(oc, pa, 3, 1);
      wg_commit();
      XSTAMP(20);
      softmax(pk, v);
      XSTAMP(21);
      wg_wait<0>();
      fence_regs(oa); fence_regs(ob); fence_regs(oc);
      XSTAMP(22);
      release(2); release(3);
      if (lane == 0) mbar_arrive(full0 + EMPTYE);
      pack16(o0, oa); pack16(o0 + 16, ob); pack16(o0 + 32, oc);
      fence_regs(o0);
    }
    {
      float oa[32], ob[32];
      early(oa, o0, 0);
      early(ob, o0, 1);
      XSTAMP(23);
      wg_wait<1>(); park(oa, 0);
      early(oa, o0, 2);
      wg_wait<1>(); park(ob, 1);
      early(ob, o0, 3);
      XSTAMP(24);
      wg_wait<1>(); park(oa, 2);
      wg_wait<0>(); park(ob, 3);
      XSTAMP(25);
      fence_regs(o0);
#pragma unroll
      for (int i = 0; i < 12; i++) o0[i] += never;
      fence_regs(o0);
      expand(pa, pk);
      pv(oa, pa, 8, 1);
      pv(ob, pa, 0, 0);
      wg_commit();
      XSTAMP(26);
      wg_wait<0>();
      fence_regs(oa); fence_regs(ob);
      XSTAMP(27);
      release(8); release(0);
      pack16(o1, oa); pack16(o1 + 16, ob);
      float oc[32];
      pv(oc, pa, 2, 0);
      wg_commit();
      XSTAMP(28);
      wg_wait<0>();
      fence_regs(oc);
      release(2);
      pack16(o1 + 32, oc);
    }
    TSTAMP(6);
  }
};

__device__ __forceinline__ uint32_t oslot_addr(uint32_t sbase, uint32_t j) { return sbase + oslot(j) * SLOT_BYTES; }
template <bool EARLY, class Mid>
__device__ __forceinline__ void oproj_chunk(float (&a)[32], const uint32_t (&o0)[48], const uint32_t (&o1)[48], int t,
                                            uint32_t d0, uint32_t d1, uint32_t fullo0, int w, uint32_t nxt, Mid mid) {
  auto tsb = [&]() { return fullo0 - FULLO + 512 + w * 128; };
  (void)tsb;
  OSTAMP(0);
  mbar_wait(fullo0 + 8 * t, 0);
  OSTAMP(1);
  if (!EARLY || t != 0 || w != FIRSTW) asm volatile("bar.sync %0, 256;" ::"r"(1 + w) : "memory");
  OSTAMP(2);
  wg_fence();
  if (!EARLY) {
    const uint64_t db = d0 | (0x40000040ull << 32);
#pragma unroll
    for (int j = 0; j < 12; j++)
      wgmma_n64_rs_tb(a, o0[4 * j], o0[4 * j + 1], o0[4 * j + 2], o0[4 * j + 3], db + 128 * j, j != 0);
  }
  {
    const uint64_t db = d1 | (0x40000040ull << 32);
#pragma unroll
    for (int j = 0; j < 12; j++) {
      wgmma_n64_rs_tb(a, o1[4 * j], o1[4 * j + 1], o1[4 * j + 2], o1[4 * j + 3], db + 128 * j, !EARLY || j != 0);
      if (j == (EARLY ? TOKEN_S : TOKEN_AT) && (EARLY || nxt)) asm volatile("bar.arrive %0, 256;" ::"r"(nxt) : "memory");
    }
    wg_commit();
  }
  OSTAMP(3);
  mid();
  OSTAMP(4);
  wg_wait<0>();
  fence_regs(a);
}

__global__ void __cluster_dims__(2, 1, 1) __launch_bounds__(NTHREADS, 1)
fused_kernel(const __grid_constant__ Params P, __nv_bfloat16* __restrict__ out) {
  extern __shared__ uint8_t smem_raw[];
  const uint32_t sbase = (smem_u32(smem_raw) + 1023u) & ~1023u;
  const uint32_t full0 = sbase + BAR_OFF;
  const uint32_t empty0 = full0 + 72;
  const uint32_t xfull0 = full0 + 144;
  const uint32_t xempty0 = full0 + 168;
  const uint32_t fullo0 = full0 + FULLO;
  const uint32_t emptyo0 = full0 + 400;
  const uint32_t eready = full0 + 344;
  const uint32_t epoch_s = full0 + 352;
  const uint32_t dtab = full0 + 480;
  const uint32_t emptye0 = full0 + EMPTYE;

  const int tid = threadIdx.x, lane = tid & 31;
  const int warp = __shfl_sync(0xffffffffu, tid >> 5, 0);
  auto tsb = [&]() { return full0 + 512 + (warp >> 2) * 128; };
  const int bid = blockIdx.x;
  const int hp = bid & 15, tg = (bid >> 4) & 3, p = bid >> 6;
  const int r = hp & 1;
  const int h0 = hp * HM;
  const int grp = p * 4 + tg;
  const int off = (hp >> 1) + (hp >> 3);
  const bool fin = r == 1 || off == 0 || off == 5;

  if (warp >= 12) {
    asm volatile("setmaxnreg.dec.sync.aligned.u32 32;");
    if (tid == 384) {
#pragma unroll
      for (int i = 2; i < NSLOT; i++) mbar_init(full0 + 8 * i, 1);
      asm volatile("fence.mbarrier_init.release.cluster;" ::: "memory");
    }
    __syncwarp();
    asm volatile("barrier.cluster.arrive.relaxed.aligned;" ::: "memory");
    if (warp == 12) {
      SNOW(sa_);
      if (lane == 0) {
#pragma unroll 1
        for (int c = 1; c < 5; c++) {
          if (c == FDELAY_C) { const uint32_t t0 = clk32(); while (clk32() - t0 < FDELAY) {} }
          mbar_expect_tx(full0 + 16 * c, SLOT_BYTES);
          tma2d(sbase + 2 * c * SLOT_BYTES, &P.x[p], c * 64, tg * 192, full0 + 16 * c);
          tma2d(sbase + 2 * c * SLOT_BYTES + 12288, &P.x[p], c * 64, tg * 192 + 96, full0 + 16 * c);
          if (c == 4) break;
          mbar_expect_tx(full0 + 8 + 16 * c, SLOT_BYTES);
          tma3d(sbase + (2 * c + 1) * SLOT_BYTES, &P.wq[p], 0, c * 64, h0 * 3, full0 + 8 + 16 * c);
        }
        asm volatile("prefetch.tensormap [%0];" ::"l"(&P.k[p]) : "memory");
        asm volatile("prefetch.tensormap [%0];" ::"l"(&P.v[p]) : "memory");
        asm volatile("prefetch.tensormap [%0];" ::"l"(&P.wo[p]) : "memory");
      }
      SNOW(sb_);
      __syncwarp();
      asm volatile("barrier.cluster.wait.aligned;" ::: "memory");
      if (lane == 0) {
        TSTAMP(3); CSTAMP(28);
        uint32_t slot = 0, phase = 1;
#pragma unroll 1
        for (int i = NSLOT; i < 49; i++) {
          mbar_wait(empty0 + 8 * slot, phase ^ 1);
          mbar_expect_tx(full0 + 8 * slot, SLOT_BYTES);
          do_item(P, i, p, tg, h0, r, sbase + slot * SLOT_BYTES, full0 + 8 * slot);
          if (++slot == NSLOT) { slot = 0; phase ^= 1; }
        }
        TSTAMP(2); CSTAMP(29);
#pragma unroll 1
        for (int e = 0; e < 23; e++) {
          int j;
          uint32_t bar;
          if (e < 11) {
            slot = (uint32_t)(0x20732087654ull >> (4 * e)) & 15u;
            if (e == 8) mbar_wait(emptye0 + 32, 0);
            else mbar_wait(empty0 + 8 * slot, e >= 5 && e < 8);
            if (e >= 4 && e < 7) {
              mbar_expect_tx(full0 + 8 * slot, SLOT_BYTES);
              do_item(P, 45 + e, p, tg, h0, r, sbase + slot * SLOT_BYTES, full0 + 8 * slot);
              continue;
            }
            j = e < 4 ? 4 * e : e - 6 + (e == 10);
          } else {
            const int n = e - 11;
            slot = oslot(n);
            mbar_wait(emptyo0 + 8 * (n >> 1), 0);
            asm volatile("fence.proxy.async.shared::cta;" ::: "memory");
            j = n + 6 + (n >= 2) + (n >= 5);
          }
          bar = e < 4 ? full0 + FULLE + 8 * e : fullo0 + 8 * (j >> 1);
          mbar_expect_tx(bar, SLOT_BYTES);
          tma2d(sbase + slot * SLOT_BYTES, &P.wo[p], chunk_of(index_at(j >> 1, r, fin), off) * 64, (h0 + HS * (j & 1)) * 192, bar);
        }
        TSTAMP(1); CSTAMP(30);
        if (fin) {
          const uint4* src = g_part + (size_t)(grp * 10 + chunk_of(8 + r, off)) * 7 * (SLOT_BYTES / 16);
#pragma unroll 1
          for (int g = 0; g < (GATHB ? 6 : 4); g++) {
            const uint32_t bar = fullo0 + 8 * (14 + (g >> 2));
            mbar_wait(emptyo0 + 8 * (6 + (g >> 1)), 0);
            asm volatile("fence.proxy.async.shared::cta;" ::: "memory");
            mbar_expect_tx(bar, SLOT_BYTES);
            TSTAMP(4 + g);
            asm volatile("cp.async.bulk.shared::cluster.global.mbarrier::complete_tx::bytes [%0], [%1], %2, [%3];"
                         ::"r"(oslot_addr(sbase, 12 + g)), "l"(src + g * (SLOT_BYTES / 16)), "r"(SLOT_BYTES), "r"(bar) : "memory");
          }
        }
      }
    } else {
      const int w = warp - 13;
      unsigned epoch;
      asm volatile("ld.global.cg.u32 %0, [%1];" : "=r"(epoch) : "l"(P.epoch + grp));
      {
        uint32_t sink = sbase + SINK_OFF + (w * 20 + lane) * 16;
        int un = 0;
        uint32_t rot = 0;
        asm volatile("barrier.cluster.wait.aligned;" ::: "memory");
        mbar_wait(full0 + 8 * PF_TRIG, 0);
        uint32_t due = clk32();
#pragma unroll 1
        for (int ph = PF0 ? -1 : 0; ph < 5; ph++) {
          const char* q;
          int nb = 4, nt = 3, nl = 16;
          uint32_t sb = 589824;
          if (ph == 1 || ph < 0) {
            q = P.wqp[p] + (size_t)(lane * 4 + tg) * 12288 + (h0 + HS * (ph > 0)) * 384 + w * 128;
            nb = 10; nt = 1; sb = 786432;
            if (ph < 0) {
              nl = 20;
              if (lane >= 16) { q = P.xp[p] + (size_t)(tg * 192 + hp * 12 + w * 4 + lane - 16) * 1280; sb = 128; }
              nb = 10 - PF0_FROM; q += PF0_FROM * sb;
            }
          } else {
            q = (ph < 3 ? P.kp[p] : P.vp[p]) + (size_t)(tg * 128 + h0 + HS * (ph == 2 || ph == 4)) * 18432 + (w * 16 + lane) * 128;
          }
#pragma unroll 1
          for (int b = 0; b < nb; b++, q += sb) {
            if (ph > 0 && mbar_test(emptye0 + 32, 0)) break;
#pragma unroll 1
            for (int t = 0; t < nt; t++) {
              if (ph < 0) asm volatile("cp.async.wait_group %0;" ::"n"(PF_WIN0 - 1) : "memory");
              else if (ph < PF_NW) asm volatile("cp.async.wait_group %0;" ::"n"(PF_WIN1 - 1) : "memory");
              else asm volatile("cp.async.wait_group %0;" ::"n"(PF_WIN - 1) : "memory");
              if (PACE) {
                while ((int)(clk32() - due) < 0) __nanosleep(32);
                due += PACE;
              }
              if (!(un & 1)) { PSTAMP(un >> 1); }
              if (lane < nl)
                asm volatile("cp.async.cg.shared.global.L2::128B [%0], [%1], 16;" ::"r"(sink + rot), "l"(q + t * 6144) : "memory");
              asm volatile("cp.async.commit_group;" ::: "memory");
              un++;
              rot = rot == (PF_DEPTH - 1) * 960 ? 0 : rot + 960;
            }
          }
          if (ph == 0) {
            if (lane < 5) {
              const int ci = 2 * lane + r, c = chunk_of(ci, off);
              asm volatile("st.shared.u32 [%0], %1;" ::"r"(dtab + 4 * lane), "r"(((grp * 10 + c) * 7 + pos_of(ci, c)) * SLOT_BYTES) : "memory");
            }
            __syncwarp();
            if (lane == 0) {
              asm volatile("st.shared.u32 [%0], %1;" ::"r"(epoch_s), "r"(epoch) : "memory");
              mbar_arrive(eready);
            }
          }
        }
#pragma unroll 1
        for (int n = WOPF0; n < WOPF; n++) {
          const int j = n + 6 - (n < -1) + (n >= 2) + (n >= 5);
          const char* q = P.wop[p] + (size_t)((h0 + HS * (j & 1)) * 192 + tg * 48 + w * 16 + lane) * 1280 + chunk_of(index_at(j >> 1, r, fin), off) * 128;
          asm volatile("cp.async.wait_group %0;" ::"n"(PF_WIN - 1) : "memory");
          while ((int)(clk32() - due) < 0) __nanosleep(32);
          due = clk32() + WOPACE;
          if (lane < 16)
            asm volatile("cp.async.cg.shared.global.L2::128B [%0], [%1], 16;" ::"r"(sink + rot), "l"(q) : "memory");
          asm volatile("cp.async.commit_group;" ::: "memory");
          rot = rot == (PF_DEPTH - 1) * 960 ? 0 : rot + 960;
        }
        asm volatile("cp.async.wait_all;" ::: "memory");
      }
    }
    __syncwarp();
    TDUMP();
  } else {
    if (tid == 0) {
      asm volatile("prefetch.tensormap [%0];" ::"l"(&P.x[p]) : "memory");
      asm volatile("prefetch.tensormap [%0];" ::"l"(&P.wq[p]) : "memory");
    }
    {
      const int c = tid & 7, rr = tid >> 3;
      const uint32_t d = sbase + rr * 128 + ((c ^ (rr & 7)) << 4);
      const char* gw = P.wqp[p] + (size_t)(rr & 15) * 12288 + (h0 * 3 + (rr >> 4)) * 128 + c * 16;
      const uint32_t dw = sbase + SLOT_BYTES + (rr >> 4) * 8192 + (rr & 15) * 128 + ((c ^ (rr & 7)) << 4);
      const char* gx = P.xp[p] + (size_t)(tg * 192 + rr) * 1280 + c * 16;
#pragma unroll
      for (int i = 0; i < 4; i++) {
        asm volatile("cp.async.cg.shared.global [%0], [%1], 16;" ::"r"(dw + i * 2048), "l"(gw + i * 196608) : "memory");
        asm volatile("cp.async.cg.shared.global [%0], [%1], 16;" ::"r"(d + i * 6144), "l"(gx + i * 61440) : "memory");
      }
    }
    if (tid == 128) {
      mbar_init(full0, 1); mbar_init(full0 + 8, 1);
      for (int i = 0; i < NSLOT; i++) mbar_init(empty0 + 8 * i, 24);
      for (int i = 0; i < 3; i++) { mbar_init(xfull0 + 8 * i, 1); mbar_init(xempty0 + 8 * i, 4); }
      for (int i = 0; i < 9; i++) mbar_init(emptyo0 + 8 * i, 12);
      mbar_init(eready, 3);
      for (int i = 0; i < 5; i++) mbar_init(emptye0 + 8 * i, 12);
      for (int i = 0; i < 16; i++) mbar_init(fullo0 + 8 * i, (0x2411112221212121ull >> (4 * i)) & 7);
      asm volatile("fence.mbarrier_init.release.cluster;" ::: "memory");
      for (int i = 0; i < 3; i++) mbar_expect_tx(xfull0 + 8 * i, XBUF_BYTES);
      mbar_arrive(full0); mbar_arrive(full0 + 8);
    }
    __syncwarp();
    asm volatile("barrier.cluster.arrive.relaxed.aligned;" ::: "memory");
    asm volatile("setmaxnreg.inc.sync.aligned.u32 160;");
    SNOW(sd_);
    asm volatile("barrier.cluster.wait.aligned;" ::: "memory");
    asm volatile("cp.async.wait_all;" ::: "memory");
    asm volatile("fence.proxy.async.shared::cta;" ::: "memory");
    asm volatile("bar.sync 4, 384;" ::: "memory");
    const int w = warp >> 2;
    const int hf = warp / 3 - w;
    uint32_t o0[48], o1[48];
    const uint32_t never = (out == nullptr);
    {
      Front f{{0, 0}, sbase, full0, mapa(empty0, lane & 1), never, w, lane, hf};
      f.run(o0, o1);
    }
#pragma unroll
    for (int i = 0; i < 12; i++) o0[i] ^= never;
    fence_regs(o0); fence_regs(o1);

    const int wt = tid & 127;
    uint32_t tok = w == 0 ? TOK0 : w == 1 ? TOK1 : TOK2;
    const uint32_t xb = sbase + XBUF_OFF + w * XBUF_BYTES + wt * 16;
    mbar_wait(eready, 0);
    uint32_t tag;
    asm volatile("ld.shared.u32 %0, [%1];" : "=r"(tag) : "r"(epoch_s) : "memory");
    tag = __shfl_sync(0xffffffffu, ~tag & 1u, 0);
    float a[32];
    uint32_t x[16];
    const uint32_t toff = w * XBUF_BYTES + wt * 16;
    uint4* dst;
    auto publish = [&]() {
#pragma unroll
      for (int j = 0; j < 4; j++)
        asm volatile("st.relaxed.gpu.global.v4.b32 [%0], {%1, %2, %3, %4};"
                     ::"l"(dst + j * 128), "r"(x[4 * j]), "r"(x[4 * j + 1]), "r"(x[4 * j + 2]), "r"(x[4 * j + 3]) : "memory");
    };
    const uint32_t dbase = ((sbase & 0x3FFFFu) >> 4) | 0x10000u;
    uint64_t tbl = OSLOTS;
    uint32_t d0 = dbase + ((uint32_t)OSLOTS & 7u) * (SLOT_BYTES / 16), d1 = dbase + ((uint32_t)(OSLOTS >> 3) & 7u) * (SLOT_BYTES / 16);
    auto mkdst = [&](int k) {
      uint32_t u;
      asm volatile("ld.shared.u32 %0, [%1];" : "=r"(u) : "r"(dtab + 4 * k) : "memory");
      dst = reinterpret_cast<uint4*>(reinterpret_cast<char*>(g_part) + (u + toff));
      asm volatile("" : "+l"(dst));
    };
    auto prepare = [&](int t, bool early) {
      const int k = t >> 1;
      if (early || (index_at(t, r, fin) & 1) != r) {
        if (k == 0) mbar_wait(empty0 + 8 * 8, 1);
        else mbar_wait(xempty0 + 8 * w, (k - 1) & 1);
        if (early) {
          load_tile(x, sbase + ((d0 - dbase) << 4) + toff);
          mkdst(k);
        }
      } else {
        RSTAMP(0);
        mbar_wait(xfull0 + 8 * w, k & 1);
        RSTAMP(1);
        load_tile(x, xb);
        if (k < 4) {
          if (wt == 0) mbar_expect_tx(xfull0 + 8 * w, XBUF_BYTES);
          __syncwarp();
          if (lane == 0) mbar_arrive_cluster(mapa(xempty0 + 8 * w, r ^ 1) + ((x[0] | x[4] | x[8] | x[12]) & never));
        } else {
          mkdst(4);
        }
      }
      tbl >>= 6;
      tok >>= 2;
      d0 = dbase + ((uint32_t)tbl & 7u) * (SLOT_BYTES / 16);
      d1 = dbase + (((uint32_t)tbl >> 3) & 7u) * (SLOT_BYTES / 16);
      fence_regs(x);
    };
    auto epilogue = [&](int t, bool early) {
      const int ci = index_at(t, r, fin);
      uint32_t z[16];
#pragma unroll
      for (int j = 0; j < 16; j++) z[j] = pack_bf16(a[2 * j], a[2 * j + 1]);
      if (early || (ci & 1) != r) {
        const uint32_t rxb = mapa(xb, r ^ 1);
        const uint32_t rbar = mapa(xfull0 + 8 * w, r ^ 1);
        if (early) {
#pragma unroll
          for (int j = 0; j < 16; j++) z[j] = add_bf16x2(z[j], x[j]);
          fence_regs(z);
        }
        if (lane == 0 && t < 9) mbar_arrive(emptyo0 + 8 * t);
#pragma unroll
        for (int j = 0; j < 4; j++)
          asm volatile("st.async.weak.shared::cluster.mbarrier::complete_tx::bytes.v4.b32 [%0], {%1, %2, %3, %4}, [%5];"
                       ::"r"(rxb + j * 2048), "r"(z[4 * j]), "r"(z[4 * j + 1]), "r"(z[4 * j + 2]), "r"(z[4 * j + 3]), "r"(rbar) : "memory");
      } else {
        if (lane == 0) mbar_arrive(emptyo0 + 8 * t);
#pragma unroll
        for (int j = 0; j < 16; j++) x[j] = add_bf16x2(z[j], x[j]);
#pragma unroll
        for (int j = 0; j < 16; j += 4) x[j] = (x[j] & ~1u) | tag;
        fence_regs(x);
        publish();
      }
      ESTAMP(20 + t);
    };
    auto finalize = [&]() {
      const int c = chunk_of(8 + r, off);
      TSTAMP(7);
      const uint4* tiles = g_part + (size_t)(grp * 10 + c) * 7 * (SLOT_BYTES / 16) + w * 512 + wt;
      auto load_g = [&](uint32_t (&y)[16], int q) {
#pragma unroll
        for (int j = 0; j < 4; j++)
          asm volatile("ld.relaxed.gpu.global.v4.b32 {%0, %1, %2, %3}, [%4];"
                       : "=r"(y[4 * j]), "=r"(y[4 * j + 1]), "=r"(y[4 * j + 2]), "=r"(y[4 * j + 3])
                       : "l"(tiles + q * (SLOT_BYTES / 16) + j * 128) : "memory");
      };
      const uint32_t tm = tag - 1u;
      const uint32_t t0 = clk32();
      auto settle = [&](uint32_t (&y)[16], int q) {
        while (true) {
          if (tile_ok(y, tm) || clk32() - t0 > SPIN_LIMIT) break;
          load_g(y, q);
        }
        add_tile(a, y);

      };
      mbar_wait(fullo0 + 8 * 14, 0);
      uint32_t ok = 1u;
#pragma unroll
      for (int j = 0; j < 4; j++) {
        uint32_t x[4][4];
#pragma unroll
        for (int q = 0; q < 4; q++)
          asm volatile("ld.shared.v4.b32 {%0, %1, %2, %3}, [%4];"
                       : "=r"(x[q][0]), "=r"(x[q][1]), "=r"(x[q][2]), "=r"(x[q][3]) : "r"(oslot_addr(sbase, 12 + q) + toff + j * 2048) : "memory");
        ok = lop3<0x80>(ok, lop3<0x42>(x[0][0], x[1][0], tm), lop3<0x42>(x[2][0], x[3][0], tm));
#pragma unroll
        for (int i = 0; i < 4; i++) {
          const uint32_t u = add_bf16x2(x[0][i], x[1][i]), v = add_bf16x2(x[2][i], x[3][i]);
          const uint32_t s = add_bf16x2(u, v);
          a[8 * j + 2 * i] = __uint_as_float(s << 16);
          a[8 * j + 2 * i + 1] = __uint_as_float(s & 0xffff0000u);
        }
      }
      if (!ok) {
#pragma unroll
        for (int j = 0; j < 32; j++) a[j] = 0.f;
#pragma unroll 1
        for (int q = 0; q < 4; q++) {
          uint32_t x[16];
          load_g(x, q);
          settle(x, q);
        }
      }
      fence_regs(a);
      ZSTAMP(30);
      mbar_wait(fullo0 + 8 * 9, 0);
      asm volatile("bar.sync %0, 256;" ::"r"(1 + w) : "memory");
      wg_fence();
      {
        const uint64_t db = make_desc(oslot_addr(sbase, 18), 16, 1024);
#pragma unroll
        for (int j = 0; j < 12; j++) wgmma_n64_rs_tb(a, o0[4 * j], o0[4 * j + 1], o0[4 * j + 2], o0[4 * j + 3], db + 128 * j, 1);
        wg_commit();
      }
      {
        const uint64_t db = make_desc(oslot_addr(sbase, 19), 16, 1024);
#pragma unroll
        for (int j = 0; j < 12; j++) {
          wgmma_n64_rs_tb(a, o1[4 * j], o1[4 * j + 1], o1[4 * j + 2], o1[4 * j + 3], db + 128 * j, 1);
          if (j == TOKEN_AT && tok) asm volatile("bar.arrive %0, 256;" ::"r"(tok) : "memory");
        }
        wg_commit();
      }
      {
        uint32_t x[16], y0[16], y1[16], y2[16];
        wg_wait<1>();
        load_g(y0, 4); load_g(y1, 5); load_g(y2, 6);
        wg_wait<0>();
        fence_regs(a);
        TSTAMP(19);
        settle(y0, 4); settle(y1, 5); settle(y2, 6);
        fence_regs(a);
        ZSTAMP(31);
        mbar_wait(xfull0 + 8 * w, 0); load_tile(x, xb);
        add_tile(a, x);
      }
      TSTAMP(8);
      const int row = tg * 192 + w * 64 + (wt >> 5) * 16 + ((wt >> 2) & 7);
      uint4* d0 = reinterpret_cast<uint4*>(out + (size_t)row * 1280 + p * 640 + c * 64 + (wt & 3) * 8);
      const bool b0 = wt & 1, b1 = wt & 2;
      __syncwarp();
#pragma unroll
      for (int u = 0; u < 4; u++) {
        uint32_t x[4];
#pragma unroll
        for (int i = 0; i < 4; i++) {
          const int j = (u & 1) * 4 + i;
          x[i] = pack_bf16(a[4 * j + (u >> 1) * 2], a[4 * j + (u >> 1) * 2 + 1]);
        }
        uint32_t v;
        v = __shfl_xor_sync(0xffffffffu, b0 ? x[0] : x[1], 1); if (b0) x[0] = v; else x[1] = v;
        v = __shfl_xor_sync(0xffffffffu, b0 ? x[2] : x[3], 1); if (b0) x[2] = v; else x[3] = v;
        v = __shfl_xor_sync(0xffffffffu, b1 ? x[0] : x[2], 2); if (b1) x[0] = v; else x[2] = v;
        v = __shfl_xor_sync(0xffffffffu, b1 ? x[1] : x[3], 2); if (b1) x[1] = v; else x[3] = v;
        d0[(u & 1) * 4 + (u >> 1) * 8 * 160] = make_uint4(x[0], x[1], x[2], x[3]);
      }
      if (hp == 1 && tid == 0) asm volatile("red.relaxed.gpu.global.add.u32 [%0], 1;" ::"l"(P.epoch + grp) : "memory");
    };
#pragma unroll 1
    for (int t = 0; t < 10; t++) {
      if (t < 8 && !(t & 1)) {
        oproj_chunk<true>(a, o0, o1, t, d0, d1, fullo0, w, tok & 3u, [&]() { prepare(t, true); });
        TSTAMP(10 + t);
        epilogue(t, true);
        t++;
      }
      if (t == 9 && fin) { finalize(); break; }
      oproj_chunk<false>(a, o0, o1, t, d0, d1, fullo0, w, tok & 3u, [&]() { prepare(t, false); });
      TSTAMP(10 + t);
      epilogue(t, false);
    }
    TSTAMP(9);
    __syncwarp();
    TDUMP();
  }
}

typedef CUresult (*EncodeFn)(CUtensorMap*, CUtensorMapDataType, cuuint32_t, void*, const cuuint64_t*, const cuuint64_t*,
                             const cuuint32_t*, const cuuint32_t*, CUtensorMapInterleave, CUtensorMapSwizzle,
                             CUtensorMapL2promotion, CUtensorMapFloatOOBfill);

static void encode(EncodeFn fn, CUtensorMap* m, const void* ptr, int rank, const cuuint64_t* dims, const cuuint64_t* strides,
                   const cuuint32_t* box) {
  cuuint32_t es[5] = {1, 1, 1, 1, 1};
  fn(m, CU_TENSOR_MAP_DATA_TYPE_BFLOAT16, (cuuint32_t)rank, const_cast<void*>(ptr), dims, strides, box, es,
     CU_TENSOR_MAP_INTERLEAVE_NONE, CU_TENSOR_MAP_SWIZZLE_128B, CU_TENSOR_MAP_L2_PROMOTION_L2_256B,
     CU_TENSOR_MAP_FLOAT_OOB_FILL_NONE);
}

}

extern "C" void kernel_launch(void* const* d_in, const int* in_sizes, int n_in, void* d_out, int out_size) {
  using namespace fk;
  static Params params;
  static const void* cached[10] = {nullptr};
  static EncodeFn fn = nullptr;
  if (!fn) {
    void* f = nullptr;
    cudaDriverEntryPointQueryResult st;
    cudaGetDriverEntryPoint("cuTensorMapEncodeTiled", &f, cudaEnableDefault, &st);
    fn = (EncodeFn)f;
    void* e = nullptr;
    cudaGetSymbolAddress(&e, g_epoch);
    params.epoch = (unsigned int*)e;
    cudaFuncSetAttribute(fused_kernel, cudaFuncAttributeMaxDynamicSharedMemorySize, SMEM_BYTES);
  }
  bool same = true;
  for (int i = 0; i < 10; i++) same = same && (cached[i] == d_in[i]);
  if (!same) {
    for (int p = 0; p < 2; p++) {
      const void* x = d_in[5 * p + 0];
      const void* k = d_in[5 * p + 1];
      const void* v = d_in[5 * p + 2];
      const void* wq = d_in[5 * p + 3];
      const void* wo = d_in[5 * p + 4];
      params.kp[p] = (const char*)k; params.vp[p] = (const char*)v;
      params.wqp[p] = (const char*)wq; params.xp[p] = (const char*)x; params.wop[p] = (const char*)wo;
      {
        cuuint64_t d[2] = {640, 768}, s[1] = {1280};
        cuuint32_t b[2] = {64, 96};
        encode(fn, &params.x[p], x, 2, d, s, b);
      }
      {
        cuuint64_t d[3] = {64, 640, 96}, s[2] = {12288, 128};
        cuuint32_t b[3] = {64, 64, 3};
        encode(fn, &params.wq[p], wq, 3, d, s, b);
      }
      {
        cuuint64_t d[4] = {192, 48, 32, 16}, s[3] = {384, 18432, 589824};
        cuuint32_t b[4] = {64, 48, 1, 4};
        encode(fn, &params.k[p], k, 4, d, s, b);
        encode(fn, &params.v[p], v, 4, d, s, b);
      }
      {
        cuuint64_t d[2] = {640, 6144}, s[1] = {1280};
        cuuint32_t b[2] = {64, 192};
        encode(fn, &params.wo[p], wo, 2, d, s, b);
      }
    }
    for (int i = 0; i < 10; i++) cached[i] = d_in[i];
  }
  fused_kernel<<<128, NTHREADS, SMEM_BYTES>>>(params, (__nv_bfloat16*)d_out);
}
```

```cpp
#include <cuda_runtime.h>
#include <cuda_bf16.h>
#include <cuda.h>
#include <stdint.h>

#define PF_ON 1
#define PF_WIN 4
#define PF_WIN1 4
#define PF_WIN0 3
#define FDELAY 500
#define FDELAY_C 1
#define NPRE 2
#define PAR 1
#define YB 1
#define GATHB 0
#define DEFER 0
#define PRE3 1
#define YFIRST 1
#define PACE 485
#define PF_TRIG 3
#define PF0_FROM 5
#define PF_NW 2
#define PF0 1
#define QMMA 4
#define TOKEN_AT 8
#define TOKEN_S 8
#define WOPF 6
#define WOPF0 -2
#define WOPACE 485
#define STAG 1
#define TOK0 0x3eaabu
#define TOK1 0x57ffdu
#define TOK2 0xa555au
#define FIRSTW 2
#define SPIN_LIMIT (1u << 27)

namespace fk {

#define HEADMAP 0
constexpr int HM = HEADMAP ? 1 : 2, HS = HEADMAP ? 16 : 1;
constexpr int SLOT_BYTES = 24576;
constexpr int NSLOT = 9;
constexpr int XBUF_BYTES = 8192;
constexpr int XBUF_OFF = 8 * SLOT_BYTES;
constexpr int BAR_OFF = NSLOT * SLOT_BYTES;
constexpr int FULLO = 192, FULLE = 272, EMPTYE = 360;
constexpr int SINK_OFF = BAR_OFF + 1024;
constexpr int PF_DEPTH = 9;
constexpr int SMEM_BYTES = SINK_OFF + PF_DEPTH * 960 + 1024;
constexpr int NTHREADS = 512;

struct Params {
  CUtensorMap x[2], wq[2], k[2], v[2], wo[2];
  const char* kp[2]; const char* vp[2]; const char* wqp[2]; const char* xp[2]; const char* wop[2];
  unsigned int* epoch;
};

__device__ uint4 g_part[8 * 10 * 7 * (SLOT_BYTES / 16)];
__device__ unsigned int g_epoch[8];
#define TSTAMP(i)
#define PSTAMP(i)
#define HSTAMP(i)
#define GSTAMP(a, b)
#define HSTAMP2(i)
#define CSTAMP(i)
#define TDUMP()

#define XSTAMP(i)
#define ESTAMP(i) TSTAMP(i)
#define QSTAMP(i)
#define RSTAMP(i)
#define OSTAMP(i)
#define ZSTAMP(i) TSTAMP(i)
#define FSTAMP(i)
#define SNOW(v)
#define SPUT(i, v)
__device__ __forceinline__ uint32_t smem_u32(const void* p) { return (uint32_t)__cvta_generic_to_shared(p); }
__device__ __forceinline__ void mbar_init(uint32_t bar, uint32_t cnt) {
  asm volatile("mbarrier.init.shared::cta.b64 [%0], %1;" ::"r"(bar), "r"(cnt) : "memory");
}
__device__ __forceinline__ void mbar_expect_tx(uint32_t bar, uint32_t bytes) {
  asm volatile("mbarrier.arrive.expect_tx.shared::cta.b64 _, [%0], %1;" ::"r"(bar), "r"(bytes) : "memory");
}
__device__ __forceinline__ uint32_t mapa(uint32_t addr, uint32_t cta) {
  uint32_t r;
  asm volatile("mapa.shared::cluster.u32 %0, %1, %2;" : "=r"(r) : "r"(addr), "r"(cta));
  return r;
}
__device__ __forceinline__ void mbar_arrive_cluster(uint32_t remote_bar) {
  asm volatile("mbarrier.arrive.shared::cluster.b64 _, [%0];" ::"r"(remote_bar) : "memory");
}
__device__ __forceinline__ uint32_t mbar_try(uint32_t bar, uint32_t parity) {
  uint32_t ok;
  asm volatile("{\n.reg .pred p;\nmbarrier.try_wait.parity.shared::cta.b64 p, [%1], %2;\nselp.u32 %0, 1, 0, p;\n}\n"
               : "=r"(ok) : "r"(bar), "r"(parity) : "memory");
  return ok;
}
__device__ __forceinline__ uint32_t mbar_test(uint32_t bar, uint32_t parity) {
  uint32_t ok;
  asm volatile("{\n.reg .pred p;\nmbarrier.test_wait.parity.shared::cta.b64 p, [%1], %2;\nselp.u32 %0, 1, 0, p;\n}\n"
               : "=r"(ok) : "r"(bar), "r"(parity) : "memory");
  return ok;
}
__device__ __forceinline__ uint32_t mbar_try_cluster(uint32_t bar, uint32_t parity) {
  uint32_t ok;
  asm volatile("{\n.reg .pred p;\nmbarrier.try_wait.parity.acquire.cluster.shared::cta.b64 p, [%1], %2;\nselp.u32 %0, 1, 0, p;\n}\n"
               : "=r"(ok) : "r"(bar), "r"(parity) : "memory");
  return ok;
}
__device__ __forceinline__ uint32_t clk32() {
  uint32_t t;
  asm volatile("mov.u32 %0, %%clock;" : "=r"(t));
  return t;
}
#define DBGREC(a, b)
__device__ __forceinline__ void mbar_wait(uint32_t bar, uint32_t parity) {
  if (mbar_try(bar, parity)) return;
  const uint32_t t0 = clk32();
  while (!mbar_try(bar, parity)) {
    if (clk32() - t0 > SPIN_LIMIT) { DBGREC(bar, parity); break; }
  }
}
__device__ __forceinline__ void mbar_wait_cluster(uint32_t bar, uint32_t parity) {
  if (mbar_try_cluster(bar, parity)) return;
  const uint32_t t0 = clk32();
  while (!mbar_try_cluster(bar, parity)) {
    if (clk32() - t0 > SPIN_LIMIT) break;
  }
}
__device__ __forceinline__ void cluster_sync() {
  asm volatile("barrier.cluster.arrive.release.aligned;\nbarrier.cluster.wait.acquire.aligned;\n" ::: "memory");
}
__device__ __forceinline__ void tma2d(uint32_t dst, const CUtensorMap* m, int c0, int c1, uint32_t bar) {
  asm volatile("cp.async.bulk.tensor.2d.shared::cluster.global.mbarrier::complete_tx::bytes [%0], [%1, {%3, %4}], [%2];"
               ::"r"(dst), "l"(m), "r"(bar), "r"(c0), "r"(c1) : "memory");
}
__device__ __forceinline__ void tma2d_mc(uint32_t dst, const CUtensorMap* m, int c0, int c1, uint32_t bar, uint16_t mask) {
  asm volatile("cp.async.bulk.tensor.2d.shared::cluster.global.mbarrier::complete_tx::bytes.multicast::cluster [%0], [%1, {%3, %4}], [%2], %5;"
               ::"r"(dst), "l"(m), "r"(bar), "r"(c0), "r"(c1), "h"(mask) : "memory");
}
__device__ __forceinline__ void tma3d(uint32_t dst, const CUtensorMap* m, int c0, int c1, int c2, uint32_t bar) {
  asm volatile("cp.async.bulk.tensor.3d.shared::cluster.global.mbarrier::complete_tx::bytes [%0], [%1, {%3, %4, %5}], [%2];"
               ::"r"(dst), "l"(m), "r"(bar), "r"(c0), "r"(c1), "r"(c2) : "memory");
}
__device__ __forceinline__ void tma4d(uint32_t dst, const CUtensorMap* m, int c0, int c1, int c2, int c3, uint32_t bar) {
  asm volatile("cp.async.bulk.tensor.4d.shared::cluster.global.mbarrier::complete_tx::bytes [%0], [%1, {%3, %4, %5, %6}], [%2];"
               ::"r"(dst), "l"(m), "r"(bar), "r"(c0), "r"(c1), "r"(c2), "r"(c3) : "memory");
}
__device__ __forceinline__ void bulk_g2s(uint32_t dst, const void* src, uint32_t bytes, uint32_t bar) {
  asm volatile("cp.async.bulk.shared::cluster.global.mbarrier::complete_tx::bytes [%0], [%1], %2, [%3];"
               ::"r"(dst), "l"(src), "r"(bytes), "r"(bar) : "memory");
}
__device__ __forceinline__ void mbar_arrive(uint32_t bar) {
  asm volatile("mbarrier.arrive.shared::cta.b64 _, [%0];" ::"r"(bar) : "memory");
}
__device__ __forceinline__ uint32_t touch_l2(const void* p) {
  uint32_t v;
  asm volatile("ld.global.cg.L2::128B.b32 %0, [%1];" : "=r"(v) : "l"(p));
  return v;
}
__device__ __forceinline__ unsigned ld_acquire(const unsigned* p) {
  unsigned v;
  asm volatile("ld.acquire.gpu.global.u32 %0, [%1];" : "=r"(v) : "l"(p) : "memory");
  return v;
}
__device__ __forceinline__ void wg_fence() { asm volatile("wgmma.fence.sync.aligned;" ::: "memory"); }
__device__ __forceinline__ void wg_commit() { asm volatile("wgmma.commit_group.sync.aligned;" ::: "memory"); }
template <int N> __device__ __forceinline__ void wg_wait() { asm volatile("wgmma.wait_group.sync.aligned %0;" ::"n"(N) : "memory"); }
template <int N> __device__ __forceinline__ void fence_regs(float (&d)[N]) {
#pragma unroll
  for (int i = 0; i < N; i++) asm volatile("" : "+f"(d[i])::"memory");
}
template <int N> __device__ __forceinline__ void fence_regs(uint32_t (&d)[N]) {
#pragma unroll
  for (int i = 0; i < N; i++) asm volatile("" : "+r"(d[i])::"memory");
}
template <int N> __device__ __forceinline__ void pin_regs(const uint32_t* d, uint32_t never, uint32_t addr) {
#pragma unroll
  for (int i = 0; i < N; i += 4)
    asm volatile("{\n.reg .pred p;\nsetp.ne.u32 p, %5, 0;\n@p st.shared.v4.b32 [%0], {%1, %2, %3, %4};\n}\n"
                 ::"r"(addr), "r"(d[i]), "r"(d[i + 1]), "r"(d[i + 2]), "r"(d[i + 3]), "r"(never) : "memory");
}
__device__ __forceinline__ uint32_t pack_bf16(float lo, float hi) {
  uint32_t r;
  asm("cvt.rn.bf16x2.f32 %0, %1, %2;" : "=r"(r) : "f"(hi), "f"(lo));
  return r;
}
__device__ __forceinline__ float ex2(float x) {
  float r;
  asm("ex2.approx.ftz.f32 %0, %1;" : "=f"(r) : "f"(x));
  return r;
}
__device__ __forceinline__ float rcp(float x) {
  float r;
  asm("rcp.approx.ftz.f32 %0, %1;" : "=f"(r) : "f"(x));
  return r;
}
__device__ __forceinline__ uint64_t make_desc(uint32_t addr, uint32_t lbo, uint32_t sbo) {
  return (uint64_t)((addr & 0x3FFFFu) >> 4) | ((uint64_t)(lbo >> 4) << 16) | ((uint64_t)(sbo >> 4) << 32) | (1ull << 62);
}

__device__ __forceinline__ void wgmma_n192_ss_tb(float (&d)[96], uint64_t da, uint64_t db, int scale_d) {
  asm volatile("{\n.reg .pred p;\nsetp.ne.b32 p, %98, 0;\n"
    "wgmma.mma_async.sync.aligned.m64n192k16.f32.bf16.bf16 "
    "{%0, %1, %2, %3, %4, %5, %6, %7, %8, %9, %10, %11, %12, %13, %14, %15, %16, %17, %18, %19, %20, %21, %22, %23, %24, %25, %26, %27, %28, %29, %30, %31, %32, %33, %34, %35, %36, %37, %38, %39, %40, %41, %42, %43, %44, %45, %46, %47, %48, %49, %50, %51, %52, %53, %54, %55, %56, %57, %58, %59, %60, %61, %62, %63, %64, %65, %66, %67, %68, %69, %70, %71, %72, %73, %74, %75, %76, %77, %78, %79, %80, %81, %82, %83, %84, %85, %86, %87, %88, %89, %90, %91, %92, %93, %94, %95}, "
    "%96, %97, p, 1, 1, 0, 1;\n}\n"
    : "+f"(d[0]), "+f"(d[1]), "+f"(d[2]), "+f"(d[3]), "+f"(d[4]), "+f"(d[5]), "+f"(d[6]), "+f"(d[7]), "+f"(d[8]), "+f"(d[9]), "+f"(d[10]), "+f"(d[11]), "+f"(d[12]), "+f"(d[13]), "+f"(d[14]), "+f"(d[15]), "+f"(d[16]), "+f"(d[17]), "+f"(d[18]), "+f"(d[19]), "+f"(d[20]), "+f"(d[21]), "+f"(d[22]), "+f"(d[23]), "+f"(d[24]), "+f"(d[25]), "+f"(d[26]), "+f"(d[27]), "+f"(d[28]), "+f"(d[29]), "+f"(d[30]), "+f"(d[31]), "+f"(d[32]), "+f"(d[33]), "+f"(d[34]), "+f"(d[35]), "+f"(d[36]), "+f"(d[37]), "+f"(d[38]), "+f"(d[39]), "+f"(d[40]), "+f"(d[41]), "+f"(d[42]), "+f"(d[43]), "+f"(d[44]), "+f"(d[45]), "+f"(d[46]), "+f"(d[47]), "+f"(d[48]), "+f"(d[49]), "+f"(d[50]), "+f"(d[51]), "+f"(d[52]), "+f"(d[53]), "+f"(d[54]), "+f"(d[55]), "+f"(d[56]), "+f"(d[57]), "+f"(d[58]), "+f"(d[59]), "+f"(d[60]), "+f"(d[61]), "+f"(d[62]), "+f"(d[63]), "+f"(d[64]), "+f"(d[65]), "+f"(d[66]), "+f"(d[67]), "+f"(d[68]), "+f"(d[69]), "+f"(d[70]), "+f"(d[71]), "+f"(d[72]), "+f"(d[73]), "+f"(d[74]), "+f"(d[75]), "+f"(d[76]), "+f"(d[77]), "+f"(d[78]), "+f"(d[79]), "+f"(d[80]), "+f"(d[81]), "+f"(d[82]), "+f"(d[83]), "+f"(d[84]), "+f"(d[85]), "+f"(d[86]), "+f"(d[87]), "+f"(d[88]), "+f"(d[89]), "+f"(d[90]), "+f"(d[91]), "+f"(d[92]), "+f"(d[93]), "+f"(d[94]), "+f"(d[95])
    : "l"(da), "l"(db), "r"(scale_d));
}
__device__ __forceinline__ void wgmma_n96_rs(float (&d)[48], uint32_t a0, uint32_t a1, uint32_t a2, uint32_t a3, uint64_t db, int scale_d) {
  asm volatile("{\n.reg .pred p;\nsetp.ne.b32 p, %53, 0;\n"
    "wgmma.mma_async.sync.aligned.m64n96k16.f32.bf16.bf16 "
    "{%0, %1, %2, %3, %4, %5, %6, %7, %8, %9, %10, %11, %12, %13, %14, %15, %16, %17, %18, %19, %20, %21, %22, %23, %24, %25, %26, %27, %28, %29, %30, %31, %32, %33, %34, %35, %36, %37, %38, %39, %40, %41, %42, %43, %44, %45, %46, %47}, "
    "{%48, %49, %50, %51}, %52, p, 1, 1, 0;\n}\n"
    : "+f"(d[0]), "+f"(d[1]), "+f"(d[2]), "+f"(d[3]), "+f"(d[4]), "+f"(d[5]), "+f"(d[6]), "+f"(d[7]), "+f"(d[8]), "+f"(d[9]), "+f"(d[10]), "+f"(d[11]), "+f"(d[12]), "+f"(d[13]), "+f"(d[14]), "+f"(d[15]), "+f"(d[16]), "+f"(d[17]), "+f"(d[18]), "+f"(d[19]), "+f"(d[20]), "+f"(d[21]), "+f"(d[22]), "+f"(d[23]), "+f"(d[24]), "+f"(d[25]), "+f"(d[26]), "+f"(d[27]), "+f"(d[28]), "+f"(d[29]), "+f"(d[30]), "+f"(d[31]), "+f"(d[32]), "+f"(d[33]), "+f"(d[34]), "+f"(d[35]), "+f"(d[36]), "+f"(d[37]), "+f"(d[38]), "+f"(d[39]), "+f"(d[40]), "+f"(d[41]), "+f"(d[42]), "+f"(d[43]), "+f"(d[44]), "+f"(d[45]), "+f"(d[46]), "+f"(d[47])
    : "r"(a0), "r"(a1), "r"(a2), "r"(a3), "l"(db), "r"(scale_d));
}
__device__ __forceinline__ void wgmma_n64_rs_tb(float (&d)[32], uint32_t a0, uint32_t a1, uint32_t a2, uint32_t a3, uint64_t db, int scale_d) {
  asm volatile("{\n.reg .pred p;\nsetp.ne.b32 p, %37, 0;\n"
    "wgmma.mma_async.sync.aligned.m64n64k16.f32.bf16.bf16 "
    "{%0, %1, %2, %3, %4, %5, %6, %7, %8, %9, %10, %11, %12, %13, %14, %15, %16, %17, %18, %19, %20, %21, %22, %23, %24, %25, %26, %27, %28, %29, %30, %31}, "
    "{%32, %33, %34, %35}, %36, p, 1, 1, 1;\n}\n"
    : "+f"(d[0]), "+f"(d[1]), "+f"(d[2]), "+f"(d[3]), "+f"(d[4]), "+f"(d[5]), "+f"(d[6]), "+f"(d[7]), "+f"(d[8]), "+f"(d[9]), "+f"(d[10]), "+f"(d[11]), "+f"(d[12]), "+f"(d[13]), "+f"(d[14]), "+f"(d[15]), "+f"(d[16]), "+f"(d[17]), "+f"(d[18]), "+f"(d[19]), "+f"(d[20]), "+f"(d[21]), "+f"(d[22]), "+f"(d[23]), "+f"(d[24]), "+f"(d[25]), "+f"(d[26]), "+f"(d[27]), "+f"(d[28]), "+f"(d[29]), "+f"(d[30]), "+f"(d[31])
    : "r"(a0), "r"(a1), "r"(a2), "r"(a3), "l"(db), "r"(scale_d));
}

__device__ __forceinline__ int chunk_of(int i, int off) { const int c = i + off; return c >= 10 ? c - 10 : c; }
__device__ __forceinline__ int pos_of(int i, int c) { return i - (i > chunk_of(c, 6)) - (i > chunk_of(c, 1)); }
#define SKEW 1
#define RSPLIT 0
__device__ __forceinline__ int index_at(int t, int r, bool both) {
  if (r == 0) return (t < 8 || both) ? (t ^ 1) : t;
  return (SKEW && !both && (t == 7 || t == 8)) ? 15 - t : t;
}

constexpr int KPOS = 43;
__device__ __forceinline__ void do_item(const Params& P, int i, int p, int tg, int h0, int r, uint32_t dst, uint32_t bar) {
  if (i >= 46) {
    const int h1 = i >= 49;
    tma4d(dst, &P.v[p], (i - 46 - 3 * h1) * 64, 0, h0 + HS * h1, tg * 4, bar);
  } else if (i >= KPOS && i < KPOS + 3) {
    tma4d(dst, &P.k[p], (i - KPOS) * 64, 0, h0 + HS, tg * 4, bar);
  } else if (i >= 20 && i < 23) {
    tma4d(dst, &P.k[p], (i - 20) * 64, 0, h0, tg * 4, bar);
  } else {
    const int hh = i >= 23;
    const int j = i - 23 * hh - 3 * (i >= KPOS);
    const int kc = j >> 1;
    if (!(j & 1)) tma2d_mc(dst + r * 12288, &P.x[p], kc * 64, tg * 192 + r * 96, bar, (uint16_t)3);
    else tma3d(dst, &P.wq[p], 0, kc * 64, (h0 + HS * hh) * 3, bar);
  }
}

struct Ring {
  uint32_t slot, phase;
  __device__ __forceinline__ void advance() {
    if (++slot == NSLOT) { slot = 0; phase ^= 1; }
  }
};

__device__ __forceinline__ void load_tile(uint32_t (&x)[16], uint32_t addr) {
#pragma unroll
  for (int j = 0; j < 4; j++)
    asm volatile("ld.shared.v4.b32 {%0, %1, %2, %3}, [%4];"
                 : "=r"(x[4 * j]), "=r"(x[4 * j + 1]), "=r"(x[4 * j + 2]), "=r"(x[4 * j + 3]) : "r"(addr + j * 2048) : "memory");
}
__device__ __forceinline__ void store_tile(uint32_t addr, const float (&a)[32]) {
#pragma unroll
  for (int j = 0; j < 4; j++)
    asm volatile("st.shared.v4.b32 [%0], {%1, %2, %3, %4};"
                 ::"r"(addr + j * 2048), "r"(pack_bf16(a[8 * j], a[8 * j + 1])), "r"(pack_bf16(a[8 * j + 2], a[8 * j + 3])),
                   "r"(pack_bf16(a[8 * j + 4], a[8 * j + 5])), "r"(pack_bf16(a[8 * j + 6], a[8 * j + 7])) : "memory");
}
__device__ __forceinline__ uint32_t add_bf16x2(uint32_t a, uint32_t b) {
  uint32_t r;
  asm("add.rn.bf16x2 %0, %1, %2;" : "=r"(r) : "r"(a), "r"(b));
  return r;
}
template <int LUT> __device__ __forceinline__ uint32_t lop3(uint32_t a, uint32_t b, uint32_t c) {
  uint32_t r;
  asm("lop3.b32 %0, %1, %2, %3, %4;" : "=r"(r) : "r"(a), "r"(b), "r"(c), "n"(LUT));
  return r;
}
__device__ __forceinline__ uint32_t tile_ok(const uint32_t (&y)[16], uint32_t tm) {
  return (y[0] ^ tm) & (y[4] ^ tm) & (y[8] ^ tm) & (y[12] ^ tm) & 1u;
}
__device__ __forceinline__ void add_tile(float (&a)[32], const uint32_t (&x)[16]) {
#pragma unroll
  for (int j = 0; j < 16; j++) {
    a[2 * j] += __uint_as_float(x[j] << 16);
    a[2 * j + 1] += __uint_as_float(x[j] & 0xffff0000u);
  }
}
constexpr uint64_t OSLOTS = 0x83d65683d6541d9ull;
__device__ __forceinline__ uint32_t oslot(uint32_t j) { return (uint32_t)(OSLOTS >> (3 * j)) & 7u; }

struct Front {
  Ring rg;
  uint32_t sbase, full0, rel0, never;
  int w, lane, hf;
  __device__ __forceinline__ uint32_t tsb() const { return full0 + 512 + w * 128; }
  __device__ __forceinline__ void release(uint32_t s) const { if (lane < 2) mbar_arrive_cluster(rel0 + 8 * s); }
  __device__ __forceinline__ uint32_t next() {
    const uint32_t s = rg.slot;
    mbar_wait(full0 + 8 * s, rg.phase);
    rg.advance();
    return s;
  }
  template <bool FIRST> __device__ __forceinline__ void qchunk(float (&acc)[96], uint32_t& sx, uint32_t& sw) {
    sx = next(); sw = next();
    const uint64_t da = make_desc(sbase + sx * SLOT_BYTES + w * 8192, 16, 1024);
    const uint64_t db = make_desc(sbase + sw * SLOT_BYTES, 8192, 1024);
    wg_fence();
#pragma unroll
    for (int s = 0; s < QMMA; s++) wgmma_n192_ss_tb(acc, da + 2 * s, db + 128 * s, !FIRST || s != 0);
    wg_commit();
  }
  __device__ __forceinline__ void qrest(float (&acc)[96], uint32_t (&qf)[48], uint32_t psx, uint32_t psw, int kc0, int tbase) {
#pragma unroll 1
    for (int kc = kc0; kc < 10; kc++) {
      uint32_t sx, sw;
      qchunk<false>(acc, sx, sw);
      QSTAMP(20 + kc);
      wg_wait<1>(); release(psx); release(psw);
      psx = sx; psw = sw;
    }
    wg_wait<0>();
    fence_regs(acc);
    release(psx); release(psw);
#pragma unroll
    for (int i = 24; i < 48; i++) qf[i] = pack_bf16(acc[2 * i], acc[2 * i + 1]);
    pin_regs<24>(qf + 24, never, full0);
#pragma unroll
    for (int i = 0; i < 24; i++) qf[i] = pack_bf16(acc[2 * i], acc[2 * i + 1]);
    pin_regs<24>(qf, never, full0);
    fence_regs(qf);
  }
  __device__ __forceinline__ void scores(float (&v)[24], const uint32_t (&qf)[48]) {
    float sacc[48];
    uint32_t ks[3];
#pragma unroll
    for (int dc = 0; dc < 3; dc++) {
      ks[dc] = next();
      const uint64_t db = make_desc(sbase + ks[dc] * SLOT_BYTES + w * 6144, 16, 1024);
      wg_fence();
#pragma unroll
      for (int s = 0; s < 4; s++) {
        const int j = dc * 4 + s;
        wgmma_n96_rs(sacc, qf[4 * j], qf[4 * j + 1], qf[4 * j + 2], qf[4 * j + 3], db + 2 * s, j != 0);
      }
    }
    wg_commit();
    wg_wait<0>();
    fence_regs(sacc);
    release(ks[0]); release(ks[1]); release(ks[2]);
#pragma unroll
    for (int i = 0; i < 24; i++) v[i] = hf ? sacc[24 + i] : sacc[i];
    fence_regs(v);
  }
  __device__ __forceinline__ void softmax(uint32_t (&pk)[12], float (&v)[24]) {
    float m0 = v[0], m1 = v[2];
#pragma unroll
    for (int t = 0; t < 6; t++) {
      m0 = fmaxf(m0, fmaxf(v[4 * t], v[4 * t + 1]));
      m1 = fmaxf(m1, fmaxf(v[4 * t + 2], v[4 * t + 3]));
    }
    m0 = fmaxf(m0, __shfl_xor_sync(0xffffffffu, m0, 1));
    m1 = fmaxf(m1, __shfl_xor_sync(0xffffffffu, m1, 1));
    m0 = fmaxf(m0, __shfl_xor_sync(0xffffffffu, m0, 2));
    m1 = fmaxf(m1, __shfl_xor_sync(0xffffffffu, m1, 2));
    const float cs = 0.07216878364870322f * 1.4426950408889634f;
    const float b0 = m0 * cs, b1 = m1 * cs;
    float s0 = 0.f, s1 = 0.f;
#pragma unroll
    for (int t = 0; t < 6; t++) {
      v[4 * t] = ex2(fmaf(v[4 * t], cs, -b0));
      v[4 * t + 1] = ex2(fmaf(v[4 * t + 1], cs, -b0));
      v[4 * t + 2] = ex2(fmaf(v[4 * t + 2], cs, -b1));
      v[4 * t + 3] = ex2(fmaf(v[4 * t + 3], cs, -b1));
      s0 += v[4 * t] + v[4 * t + 1];
      s1 += v[4 * t + 2] + v[4 * t + 3];
    }
    s0 += __shfl_xor_sync(0xffffffffu, s0, 1);
    s1 += __shfl_xor_sync(0xffffffffu, s1, 1);
    s0 += __shfl_xor_sync(0xffffffffu, s0, 2);
    s1 += __shfl_xor_sync(0xffffffffu, s1, 2);
    const float r0 = rcp(s0), r1 = rcp(s1);
#pragma unroll
    for (int t = 0; t < 6; t++) {
      pk[2 * t] = pack_bf16(v[4 * t] * r0, v[4 * t + 1] * r0);
      pk[2 * t + 1] = pack_bf16(v[4 * t + 2] * r1, v[4 * t + 3] * r1);
    }
    pin_regs<12>(pk, never, full0);
    fence_regs(pk);
  }
  __device__ __forceinline__ void expand(uint32_t (&pa)[24], uint32_t (&pk)[12]) {
    fence_regs(pk);
#pragma unroll
    for (int i = 0; i < 12; i++) {
      pa[i] = hf ? 0u : pk[i];
      pa[12 + i] = hf ? pk[i] : 0u;
    }
    fence_regs(pa);
  }
  __device__ __forceinline__ void pv(float (&oa)[32], const uint32_t (&pa)[24], int s, int parity) {
    mbar_wait(full0 + 8 * s, parity);
    const uint64_t db = make_desc(sbase + s * SLOT_BYTES + w * 6144, 16, 1024);
    wg_fence();
#pragma unroll
    for (int j = 0; j < 6; j++) wgmma_n64_rs_tb(oa, pa[4 * j], pa[4 * j + 1], pa[4 * j + 2], pa[4 * j + 3], db + 128 * j, j != 0);
  }
  __device__ __forceinline__ void pack16(uint32_t* o, const float (&oa)[32]) {
#pragma unroll
    for (int i = 0; i < 16; i++) o[i] = pack_bf16(oa[2 * i], oa[2 * i + 1]);
    pin_regs<16>(o, never, full0);
  }
  __device__ __forceinline__ void early(float (&a)[32], const uint32_t (&o0)[48], int t) {
    mbar_wait(full0 + FULLE + 8 * t, 0);
    const uint64_t db = make_desc(sbase + (4 + t) * SLOT_BYTES, 16, 1024);
    wg_fence();
#pragma unroll
    for (int j = 0; j < 12; j++)
      wgmma_n64_rs_tb(a, o0[4 * j], o0[4 * j + 1], o0[4 * j + 2], o0[4 * j + 3], db + 128 * j, j != 0);
    wg_commit();
  }
  __device__ __forceinline__ void park(float (&a)[32], int t) {
    fence_regs(a);
    if (lane == 0) mbar_arrive(full0 + EMPTYE + 8 * (t + 1));
    mbar_wait(full0 + EMPTYE + 8 * t, 0);
    uint32_t tid;
    asm volatile("mov.u32 %0, %%tid.x;" : "=r"(tid));
    store_tile(sbase + oslot(4 * t) * SLOT_BYTES + (tid >> 7) * XBUF_BYTES + (tid & 127) * 16, a);
  }
  __device__ __forceinline__ void run(uint32_t (&o0)[48], uint32_t (&o1)[48]) {
    uint32_t pk[12], pa[24];
    float v[24];
    {
      uint32_t qf[48];
      {
        float acc[96];
        uint32_t sx, sw;
        qchunk<true>(acc, sx, sw);
        { const int tbase = 1; (void)tbase; QSTAMP(20); }
        qrest(acc, qf, sx, sw, 1, 1);
      }
      TSTAMP(1);
      scores(v, qf);
      TSTAMP(2);
    }
    {
      uint32_t qf[48];
      {
        float acc[96];
        uint32_t ax, aw, bx, bw;
        qchunk<true>(acc, ax, aw);
        qchunk<false>(acc, bx, bw);
        softmax(pk, v);
        TSTAMP(3);
        wg_wait<1>(); release(ax); release(aw);
        qrest(acc, qf, bx, bw, 2, 4);
      }
      TSTAMP(4);
      scores(v, qf);
      TSTAMP(5);
    }
    {
      float oa[32], ob[32], oc[32];
      expand(pa, pk);
      pv(oa, pa, 1, 1); pv(ob, pa, 2, 1); pv(oc, pa, 3, 1);
      wg_commit();
      XSTAMP(20);
      softmax(pk, v);
      XSTAMP(21);
      wg_wait<0>();
      fence_regs(oa); fence_regs(ob); fence_regs(oc);
      XSTAMP(22);
      release(2); release(3);
      if (lane == 0) mbar_arrive(full0 + EMPTYE);
      pack16(o0, oa); pack16(o0 + 16, ob); pack16(o0 + 32, oc);
      fence_regs(o0);
    }
    {
      float oa[32], ob[32];
      early(oa, o0, 0);
      early(ob, o0, 1);
      XSTAMP(23);
      wg_wait<1>(); park(oa, 0);
      early(oa, o0, 2);
      wg_wait<1>(); park(ob, 1);
      early(ob, o0, 3);
      XSTAMP(24);
      wg_wait<1>(); park(oa, 2);
      wg_wait<0>(); park(ob, 3);
      XSTAMP(25);
      fence_regs(o0);
#pragma unroll
      for (int i = 0; i < 12; i++) o0[i] += never;
      fence_regs(o0);
      expand(pa, pk);
      pv(oa, pa, 8, 1);
      pv(ob, pa, 0, 0);
      wg_commit();
      XSTAMP(26);
      wg_wait<0>();
      fence_regs(oa); fence_regs(ob);
      XSTAMP(27);
      release(8); release(0);
      pack16(o1, oa); pack16(o1 + 16, ob);
      float oc[32];
      pv(oc, pa, 2, 0);
      wg_commit();
      XSTAMP(28);
      wg_wait<0>();
      fence_regs(oc);
      release(2);
      pack16(o1 + 32, oc);
    }
    TSTAMP(6);
  }
};

__device__ __forceinline__ uint32_t oslot_addr(uint32_t sbase, uint32_t j) { return sbase + oslot(j) * SLOT_BYTES; }
template <bool EARLY, class Mid>
__device__ __forceinline__ void oproj_chunk(float (&a)[32], const uint32_t (&o0)[48], const uint32_t (&o1)[48], int t,
                                            uint32_t d0, uint32_t d1, uint32_t fullo0, int w, uint32_t nxt, Mid mid) {
  auto tsb = [&]() { return fullo0 - FULLO + 512 + w * 128; };
  (void)tsb;
  OSTAMP(0);
  mbar_wait(fullo0 + 8 * t, 0);
  OSTAMP(1);
  if (!EARLY || t != 0 || w != FIRSTW) asm volatile("bar.sync %0, 256;" ::"r"(1 + w) : "memory");
  OSTAMP(2);
  wg_fence();
  if (!EARLY) {
    const uint64_t db = d0 | (0x40000040ull << 32);
#pragma unroll
    for (int j = 0; j < 12; j++)
      wgmma_n64_rs_tb(a, o0[4 * j], o0[4 * j + 1], o0[4 * j + 2], o0[4 * j + 3], db + 128 * j, j != 0);
  }
  {
    const uint64_t db = d1 | (0x40000040ull << 32);
#pragma unroll
    for (int j = 0; j < 12; j++) {
      wgmma_n64_rs_tb(a, o1[4 * j], o1[4 * j + 1], o1[4 * j + 2], o1[4 * j + 3], db + 128 * j, !EARLY || j != 0);
      if (j == (EARLY ? TOKEN_S : TOKEN_AT) && (EARLY || nxt)) asm volatile("bar.arrive %0, 256;" ::"r"(nxt) : "memory");
    }
    wg_commit();
  }
  OSTAMP(3);
  mid();
  OSTAMP(4);
  wg_wait<0>();
  fence_regs(a);
}

__global__ void __cluster_dims__(2, 1, 1) __launch_bounds__(NTHREADS, 1)
fused_kernel(const __grid_constant__ Params P, __nv_bfloat16* __restrict__ out) {
  extern __shared__ uint8_t smem_raw[];
  const uint32_t sbase = (smem_u32(smem_raw) + 1023u) & ~1023u;
  const uint32_t full0 = sbase + BAR_OFF;
  const uint32_t empty0 = full0 + 72;
  const uint32_t xfull0 = full0 + 144;
  const uint32_t xempty0 = full0 + 168;
  const uint32_t fullo0 = full0 + FULLO;
  const uint32_t emptyo0 = full0 + 400;
  const uint32_t eready = full0 + 344;
  const uint32_t epoch_s = full0 + 352;
  const uint32_t dtab = full0 + 480;
  const uint32_t emptye0 = full0 + EMPTYE;

  const int tid = threadIdx.x, lane = tid & 31;
  const int warp = __shfl_sync(0xffffffffu, tid >> 5, 0);
  auto tsb = [&]() { return full0 + 512 + (warp >> 2) * 128; };
  const int bid = blockIdx.x;
  const int hp = bid & 15, tg = (bid >> 4) & 3, p = bid >> 6;
  const int r = hp & 1;
  const int h0 = hp * HM;
  const int grp = p * 4 + tg;
  const int off = (hp >> 1) + (hp >> 3);
  const bool both = off == 0 || off == 5;
  const bool fin = r == 1 || both;

  if (warp >= 12) {
    asm volatile("setmaxnreg.dec.sync.aligned.u32 32;");
    if (tid == 384) {
#pragma unroll
      for (int i = 2; i < NSLOT; i++) mbar_init(full0 + 8 * i, 1);
      asm volatile("fence.mbarrier_init.release.cluster;" ::: "memory");
    }
    __syncwarp();
    asm volatile("barrier.cluster.arrive.relaxed.aligned;" ::: "memory");
    if (warp == 12) {
      SNOW(sa_);
      if (lane == 0) {
#pragma unroll 1
        for (int c = 1; c < 5; c++) {
          if (c == FDELAY_C) { const uint32_t t0 = clk32(); while (clk32() - t0 < FDELAY) {} }
          mbar_expect_tx(full0 + 16 * c, SLOT_BYTES);
          tma2d(sbase + 2 * c * SLOT_BYTES, &P.x[p], c * 64, tg * 192, full0 + 16 * c);
          tma2d(sbase + 2 * c * SLOT_BYTES + 12288, &P.x[p], c * 64, tg * 192 + 96, full0 + 16 * c);
          if (c == 4) break;
          mbar_expect_tx(full0 + 8 + 16 * c, SLOT_BYTES);
          tma3d(sbase + (2 * c + 1) * SLOT_BYTES, &P.wq[p], 0, c * 64, h0 * 3, full0 + 8 + 16 * c);
        }
        asm volatile("prefetch.tensormap [%0];" ::"l"(&P.k[p]) : "memory");
        asm volatile("prefetch.tensormap [%0];" ::"l"(&P.v[p]) : "memory");
        asm volatile("prefetch.tensormap [%0];" ::"l"(&P.wo[p]) : "memory");
      }
      SNOW(sb_);
      __syncwarp();
      asm volatile("barrier.cluster.wait.aligned;" ::: "memory");
      if (lane == 0) {
        TSTAMP(3); CSTAMP(28);
        uint32_t slot = 0, phase = 1;
#pragma unroll 1
        for (int i = NSLOT; i < 49; i++) {
          mbar_wait(empty0 + 8 * slot, phase ^ 1);
          mbar_expect_tx(full0 + 8 * slot, SLOT_BYTES);
          do_item(P, i, p, tg, h0, r, sbase + slot * SLOT_BYTES, full0 + 8 * slot);
          if (++slot == NSLOT) { slot = 0; phase ^= 1; }
        }
        TSTAMP(2); CSTAMP(29);
#pragma unroll 1
        for (int e = 0; e < 23; e++) {
          int j;
          uint32_t bar;
          if (e < 11) {
            slot = (uint32_t)(0x20732087654ull >> (4 * e)) & 15u;
            if (e == 8) mbar_wait(emptye0 + 32, 0);
            else mbar_wait(empty0 + 8 * slot, e >= 5 && e < 8);
            if (e >= 4 && e < 7) {
              mbar_expect_tx(full0 + 8 * slot, SLOT_BYTES);
              do_item(P, 45 + e, p, tg, h0, r, sbase + slot * SLOT_BYTES, full0 + 8 * slot);
              continue;
            }
            j = e < 4 ? 4 * e : e - 6 + (e == 10);
          } else {
            const int n = e - 11;
            slot = oslot(n);
            mbar_wait(emptyo0 + 8 * (n >> 1), 0);
            asm volatile("fence.proxy.async.shared::cta;" ::: "memory");
            j = n + 6 + (n >= 2) + (n >= 5);
          }
          bar = e < 4 ? full0 + FULLE + 8 * e : fullo0 + 8 * (j >> 1);
          mbar_expect_tx(bar, SLOT_BYTES);
          tma2d(sbase + slot * SLOT_BYTES, &P.wo[p], chunk_of(index_at(j >> 1, r, both), off) * 64, (h0 + HS * (j & 1)) * 192, bar);
        }
        TSTAMP(1); CSTAMP(30);
        if (fin || RSPLIT) {
          const int lo = RSPLIT && !fin ? 2 * XBUF_BYTES : 0, hi = RSPLIT && !both && r ? 2 * XBUF_BYTES : 3 * XBUF_BYTES;
          const char* src = reinterpret_cast<const char*>(g_part) + (size_t)(grp * 10 + chunk_of(both ? 8 + r : 9, off)) * 7 * SLOT_BYTES;
          mbar_wait(emptyo0 + 8 * 6, 0);
          asm volatile("fence.proxy.async.shared::cta;" ::: "memory");
          mbar_expect_tx(fullo0 + 8 * 14, 2 * (hi - lo));
          TSTAMP(4);
          bulk_g2s(oslot_addr(sbase, 12) + lo, src + lo, hi - lo, fullo0 + 8 * 14);
          bulk_g2s(oslot_addr(sbase, 13) + lo, src + SLOT_BYTES + lo, hi - lo, fullo0 + 8 * 14);
          TSTAMP(5);
          mbar_wait(emptyo0 + 8 * 7, 0);
          asm volatile("fence.proxy.async.shared::cta;" ::: "memory");
          TSTAMP(6);
#pragma unroll 1
          for (int u = hi - XBUF_BYTES; u >= lo; u -= XBUF_BYTES) {
            const uint32_t bar = fullo0 + 8 * 16 + (u >> 10);
            mbar_expect_tx(bar, 2 * XBUF_BYTES);
            bulk_g2s(oslot_addr(sbase, 14) + u, src + 2 * SLOT_BYTES + u, XBUF_BYTES, bar);
            bulk_g2s(oslot_addr(sbase, 15) + u, src + 3 * SLOT_BYTES + u, XBUF_BYTES, bar);
          }
          TSTAMP(7);
        }
      }
    } else {
      const int w = warp - 13;
      unsigned epoch;
      asm volatile("ld.global.cg.u32 %0, [%1];" : "=r"(epoch) : "l"(P.epoch + grp));
      {
        uint32_t sink = sbase + SINK_OFF + (w * 20 + lane) * 16;
        int un = 0;
        uint32_t rot = 0;
        asm volatile("barrier.cluster.wait.aligned;" ::: "memory");
        mbar_wait(full0 + 8 * PF_TRIG, 0);
        uint32_t due = clk32();
#pragma unroll 1
        for (int ph = PF0 ? -1 : 0; ph < 5; ph++) {
          const char* q;
          int nb = 4, nt = 3, nl = 16;
          uint32_t sb = 589824;
          if (ph == 1 || ph < 0) {
            q = P.wqp[p] + (size_t)(lane * 4 + tg) * 12288 + (h0 + HS * (ph > 0)) * 384 + w * 128;
            nb = 10; nt = 1; sb = 786432;
            if (ph < 0) {
              nl = 20;
              if (lane >= 16) { q = P.xp[p] + (size_t)(tg * 192 + hp * 12 + w * 4 + lane - 16) * 1280; sb = 128; }
              nb = 10 - PF0_FROM; q += PF0_FROM * sb;
            }
          } else {
            q = (ph < 3 ? P.kp[p] : P.vp[p]) + (size_t)(tg * 128 + h0 + HS * (ph == 2 || ph == 4)) * 18432 + (w * 16 + lane) * 128;
          }
#pragma unroll 1
          for (int b = 0; b < nb; b++, q += sb) {
            if (ph > 0 && mbar_test(emptye0 + 32, 0)) break;
#pragma unroll 1
            for (int t = 0; t < nt; t++) {
              if (ph < 0) asm volatile("cp.async.wait_group %0;" ::"n"(PF_WIN0 - 1) : "memory");
              else if (ph < PF_NW) asm volatile("cp.async.wait_group %0;" ::"n"(PF_WIN1 - 1) : "memory");
              else asm volatile("cp.async.wait_group %0;" ::"n"(PF_WIN - 1) : "memory");
              if (PACE) {
                while ((int)(clk32() - due) < 0) __nanosleep(32);
                due += PACE;
              }
              if (!(un & 1)) { PSTAMP(un >> 1); }
              if (lane < nl)
                asm volatile("cp.async.cg.shared.global.L2::128B [%0], [%1], 16;" ::"r"(sink + rot), "l"(q + t * 6144) : "memory");
              asm volatile("cp.async.commit_group;" ::: "memory");
              un++;
              rot = rot == (PF_DEPTH - 1) * 960 ? 0 : rot + 960;
            }
          }
          if (ph == 0) {
            if (lane < 5) {
              const int ci = 2 * lane + r, c = chunk_of(ci, off);
              asm volatile("st.shared.u32 [%0], %1;" ::"r"(dtab + 4 * lane), "r"(((grp * 10 + c) * 7 + pos_of(ci, c)) * SLOT_BYTES) : "memory");
            }
            __syncwarp();
            if (lane == 0) {
              asm volatile("st.shared.u32 [%0], %1;" ::"r"(epoch_s), "r"(epoch) : "memory");
              mbar_arrive(eready);
            }
          }
        }
#pragma unroll 1
        for (int n = WOPF0; n < WOPF; n++) {
          const int j = n + 6 - (n < -1) + (n >= 2) + (n >= 5);
          const char* q = P.wop[p] + (size_t)((h0 + HS * (j & 1)) * 192 + tg * 48 + w * 16 + lane) * 1280 + chunk_of(index_at(j >> 1, r, both), off) * 128;
          asm volatile("cp.async.wait_group %0;" ::"n"(PF_WIN - 1) : "memory");
          while ((int)(clk32() - due) < 0) __nanosleep(32);
          due = clk32() + WOPACE;
          if (lane < 16)
            asm volatile("cp.async.cg.shared.global.L2::128B [%0], [%1], 16;" ::"r"(sink + rot), "l"(q) : "memory");
          asm volatile("cp.async.commit_group;" ::: "memory");
          rot = rot == (PF_DEPTH - 1) * 960 ? 0 : rot + 960;
        }
        asm volatile("cp.async.wait_all;" ::: "memory");
      }
    }
    __syncwarp();
    TDUMP();
  } else {
    if (tid == 0) {
      asm volatile("prefetch.tensormap [%0];" ::"l"(&P.x[p]) : "memory");
      asm volatile("prefetch.tensormap [%0];" ::"l"(&P.wq[p]) : "memory");
    }
    {
      const int c = tid & 7, rr = tid >> 3;
      const uint32_t d = sbase + rr * 128 + ((c ^ (rr & 7)) << 4);
      const char* gw = P.wqp[p] + (size_t)(rr & 15) * 12288 + (h0 * 3 + (rr >> 4)) * 128 + c * 16;
      const uint32_t dw = sbase + SLOT_BYTES + (rr >> 4) * 8192 + (rr & 15) * 128 + ((c ^ (rr & 7)) << 4);
      const char* gx = P.xp[p] + (size_t)(tg * 192 + rr) * 1280 + c * 16;
#pragma unroll
      for (int i = 0; i < 4; i++) {
        asm volatile("cp.async.cg.shared.global [%0], [%1], 16;" ::"r"(dw + i * 2048), "l"(gw + i * 196608) : "memory");
        asm volatile("cp.async.cg.shared.global [%0], [%1], 16;" ::"r"(d + i * 6144), "l"(gx + i * 61440) : "memory");
      }
    }
    if (tid == 128) {
      mbar_init(full0, 1); mbar_init(full0 + 8, 1);
      for (int i = 0; i < NSLOT; i++) mbar_init(empty0 + 8 * i, 24);
      for (int i = 0; i < 3; i++) { mbar_init(xfull0 + 8 * i, 1); mbar_init(xempty0 + 8 * i, 4); }
      for (int i = 0; i < 9; i++) mbar_init(emptyo0 + 8 * i, 12);
      mbar_init(eready, 3);
      for (int i = 0; i < 5; i++) mbar_init(emptye0 + 8 * i, 12);
      for (int i = 0; i < 19; i++) mbar_init(fullo0 + 8 * i, 1 + ((0x3aau >> i) & 1));
      asm volatile("fence.mbarrier_init.release.cluster;" ::: "memory");
      for (int i = 0; i < 3; i++) mbar_expect_tx(xfull0 + 8 * i, XBUF_BYTES);
      mbar_arrive(full0); mbar_arrive(full0 + 8);
    }
    __syncwarp();
    asm volatile("barrier.cluster.arrive.relaxed.aligned;" ::: "memory");
    asm volatile("setmaxnreg.inc.sync.aligned.u32 160;");
    SNOW(sd_);
    asm volatile("barrier.cluster.wait.aligned;" ::: "memory");
    asm volatile("cp.async.wait_all;" ::: "memory");
    asm volatile("fence.proxy.async.shared::cta;" ::: "memory");
    asm volatile("bar.sync 4, 384;" ::: "memory");
    const int w = warp >> 2;
    const int hf = warp / 3 - w;
    uint32_t o0[48], o1[48];
    const uint32_t never = (out == nullptr);
    {
      Front f{{0, 0}, sbase, full0, mapa(empty0, lane & 1), never, w, lane, hf};
      f.run(o0, o1);
    }
#pragma unroll
    for (int i = 0; i < 12; i++) o0[i] ^= never;
    fence_regs(o0); fence_regs(o1);

    const int wt = tid & 127;
    uint32_t tok = w == 0 ? TOK0 : w == 1 ? TOK1 : TOK2;
    const bool finw = RSPLIT ? both || (r == 1) != (w == 2) : fin;
    if (RSPLIT && !fin) tok = w == 0 ? 0xfaaabu : w == 1 ? TOK1 : 0x2555au;
    const uint32_t xb = sbase + XBUF_OFF + w * XBUF_BYTES + wt * 16;
    mbar_wait(eready, 0);
    uint32_t tag;
    asm volatile("ld.shared.u32 %0, [%1];" : "=r"(tag) : "r"(epoch_s) : "memory");
    tag = __shfl_sync(0xffffffffu, ~tag & 1u, 0);
    float a[32];
    uint32_t x[16];
    const uint32_t toff = w * XBUF_BYTES + wt * 16;
    uint4* dst;
    auto publish = [&]() {
#pragma unroll
      for (int j = 0; j < 4; j++)
        asm volatile("st.relaxed.gpu.global.v4.b32 [%0], {%1, %2, %3, %4};"
                     ::"l"(dst + j * 128), "r"(x[4 * j]), "r"(x[4 * j + 1]), "r"(x[4 * j + 2]), "r"(x[4 * j + 3]) : "memory");
    };
    const uint32_t dbase = ((sbase & 0x3FFFFu) >> 4) | 0x10000u;
    uint64_t tbl = OSLOTS;
    uint32_t d0 = dbase + ((uint32_t)OSLOTS & 7u) * (SLOT_BYTES / 16), d1 = dbase + ((uint32_t)(OSLOTS >> 3) & 7u) * (SLOT_BYTES / 16);
    auto mkdst = [&](int k) {
      uint32_t u;
      asm volatile("ld.shared.u32 %0, [%1];" : "=r"(u) : "r"(dtab + 4 * k) : "memory");
      dst = reinterpret_cast<uint4*>(reinterpret_cast<char*>(g_part) + (u + toff));
      asm volatile("" : "+l"(dst));
    };
    auto prepare = [&](int t, bool early) {
      const int ci = index_at(t, r, both);
      const int k = early ? t >> 1 : (ci >> 1) + (RSPLIT && t == 9 && r);
      if (early || (ci & 1) != r || t == 9) {
        if (k == 0) mbar_wait(empty0 + 8 * 8, 1);
        else mbar_wait(xempty0 + 8 * w, (k - 1) & 1);
        if (early) {
          load_tile(x, sbase + ((d0 - dbase) << 4) + toff);
          mkdst(k);
        }
      } else {
        RSTAMP(0);
        mbar_wait(xfull0 + 8 * w, k & 1);
        RSTAMP(1);
        load_tile(x, xb);
        if (k < 4 || finw) {
          if (wt == 0) mbar_expect_tx(xfull0 + 8 * w, XBUF_BYTES);
          __syncwarp();
          if (lane == 0) mbar_arrive_cluster(mapa(xempty0 + 8 * w, r ^ 1) + ((x[0] | x[4] | x[8] | x[12]) & never));
        }
        if (k == 4) mkdst(4);
      }
      tbl >>= 6;
      tok >>= 2;
      d0 = dbase + ((uint32_t)tbl & 7u) * (SLOT_BYTES / 16);
      d1 = dbase + (((uint32_t)tbl >> 3) & 7u) * (SLOT_BYTES / 16);
      fence_regs(x);
    };
    auto epilogue = [&](int t, bool early) {
      const int ci = index_at(t, r, both);
      uint32_t z[16];
#pragma unroll
      for (int j = 0; j < 16; j++) z[j] = pack_bf16(a[2 * j], a[2 * j + 1]);
      if (early || (ci & 1) != r || t == 9) {
        const uint32_t rxb = mapa(xb, r ^ 1);
        const uint32_t rbar = mapa(xfull0 + 8 * w, r ^ 1);
        if (early) {
#pragma unroll
          for (int j = 0; j < 16; j++) z[j] = add_bf16x2(z[j], x[j]);
          fence_regs(z);
        }
        if (lane == 0 && t < 9) mbar_arrive(emptyo0 + 8 * t);
#pragma unroll
        for (int j = 0; j < 4; j++)
          asm volatile("st.async.weak.shared::cluster.mbarrier::complete_tx::bytes.v4.b32 [%0], {%1, %2, %3, %4}, [%5];"
                       ::"r"(rxb + j * 2048), "r"(z[4 * j]), "r"(z[4 * j + 1]), "r"(z[4 * j + 2]), "r"(z[4 * j + 3]), "r"(rbar) : "memory");
      } else {
        if (lane == 0) mbar_arrive(emptyo0 + 8 * t);
#pragma unroll
        for (int j = 0; j < 16; j++) x[j] = add_bf16x2(z[j], x[j]);
#pragma unroll
        for (int j = 0; j < 16; j += 4) x[j] = (x[j] & ~1u) | tag;
        fence_regs(x);
        publish();
      }
      ESTAMP(20 + t);
    };
    auto finalize = [&]() {
      const int c = chunk_of(both ? 8 + r : 9, off);
      TSTAMP(7);
      const uint4* tiles = g_part + (size_t)(grp * 10 + c) * 7 * (SLOT_BYTES / 16) + w * 512 + wt;
      auto load_g = [&](uint32_t (&y)[16], int q) {
#pragma unroll
        for (int j = 0; j < 4; j++)
          asm volatile("ld.relaxed.gpu.global.v4.b32 {%0, %1, %2, %3}, [%4];"
                       : "=r"(y[4 * j]), "=r"(y[4 * j + 1]), "=r"(y[4 * j + 2]), "=r"(y[4 * j + 3])
                       : "l"(tiles + q * (SLOT_BYTES / 16) + j * 128) : "memory");
      };
      const uint32_t tm = tag - 1u;
      const uint32_t t0 = clk32();
      auto settle = [&](uint32_t (&y)[16], int q) {
        while (true) {
          if (tile_ok(y, tm) || clk32() - t0 > SPIN_LIMIT) break;
          load_g(y, q);
        }
        add_tile(a, y);

      };
      mbar_wait(fullo0 + 8 * 14, 0);
      uint32_t ok = 1u;
#pragma unroll
      for (int h = 0; h < NPRE; h++) {
        if (h) {
          fence_regs(x);
          mbar_wait(fullo0 + 8 * (16 + w), 0);
        }
#pragma unroll
        for (int j = 0; j < 4; j++) {
          uint32_t y[2][4];
#pragma unroll
          for (int q = 0; q < 2; q++)
            asm volatile("ld.shared.v4.b32 {%0, %1, %2, %3}, [%4];"
                         : "=r"(y[q][0]), "=r"(y[q][1]), "=r"(y[q][2]), "=r"(y[q][3])
                         : "r"(oslot_addr(sbase, 12 + 2 * h + q) + toff + j * 2048) : "memory");
          ok &= lop3<0x42>(y[0][0], y[1][0], tm);
#pragma unroll
          for (int i = 0; i < 4; i++) {
            const uint32_t u = add_bf16x2(y[0][i], y[1][i]);
            if (!h) {
              x[4 * j + i] = u;
            } else {
              const uint32_t s = add_bf16x2(x[4 * j + i], u);
              a[8 * j + 2 * i] = __uint_as_float(s << 16);
              a[8 * j + 2 * i + 1] = __uint_as_float(s & 0xffff0000u);
            }
          }
        }
      }
      if (!ok) {
#pragma unroll
        for (int j = 0; j < 32; j++) a[j] = 0.f;
#pragma unroll 1
        for (int q = 0; q < 4; q++) {
          uint32_t x[16];
          load_g(x, q);
          settle(x, q);
        }
      }
      fence_regs(a);
      ZSTAMP(30);
      mbar_wait(fullo0 + 8 * 9, 0);
      asm volatile("bar.sync %0, 256;" ::"r"(1 + w) : "memory");
      wg_fence();
      {
        const uint64_t db = make_desc(oslot_addr(sbase, 18), 16, 1024);
#pragma unroll
        for (int j = 0; j < 12; j++) wgmma_n64_rs_tb(a, o0[4 * j], o0[4 * j + 1], o0[4 * j + 2], o0[4 * j + 3], db + 128 * j, 1);
        wg_commit();
      }
      {
        const uint64_t db = make_desc(oslot_addr(sbase, 19), 16, 1024);
#pragma unroll
        for (int j = 0; j < 12; j++) {
          wgmma_n64_rs_tb(a, o1[4 * j], o1[4 * j + 1], o1[4 * j + 2], o1[4 * j + 3], db + 128 * j, 1);
          if (j == TOKEN_AT && tok) asm volatile("bar.arrive %0, 256;" ::"r"(tok) : "memory");
        }
        wg_commit();
      }
      {
        uint32_t x[16], y0[16], y1[16], y2[16];
        wg_wait<1>();
        load_g(y0, 4); load_g(y1, 5); load_g(y2, 6);
        wg_wait<0>();
        fence_regs(a);
        TSTAMP(19);
        while (true) {
          const uint32_t k0 = tile_ok(y0, tm), k1 = tile_ok(y1, tm), k2 = tile_ok(y2, tm);
          if ((k0 & k1 & k2) || clk32() - t0 > SPIN_LIMIT) break;
          if (!k0) load_g(y0, 4);
          if (!k1) load_g(y1, 5);
          if (!k2) load_g(y2, 6);
        }
#pragma unroll
        for (int j = 0; j < 16; j++) y0[j] = add_bf16x2(add_bf16x2(y0[j], y1[j]), y2[j]);
        add_tile(a, y0);
        fence_regs(a);
        ZSTAMP(31);
        mbar_wait(xfull0 + 8 * w, !fin); load_tile(x, xb);
        add_tile(a, x);
      }
      TSTAMP(8);
      const int row = tg * 192 + w * 64 + (wt >> 5) * 16 + ((wt >> 2) & 7);
      uint4* d0 = reinterpret_cast<uint4*>(out + (size_t)row * 1280 + p * 640 + c * 64 + (wt & 3) * 8);
      const bool b0 = wt & 1, b1 = wt & 2;
      __syncwarp();
#pragma unroll
      for (int u = 0; u < 4; u++) {
        uint32_t x[4];
#pragma unroll
        for (int i = 0; i < 4; i++) {
          const int j = (u & 1) * 4 + i;
          x[i] = pack_bf16(a[4 * j + (u >> 1) * 2], a[4 * j + (u >> 1) * 2 + 1]);
        }
        uint32_t v;
        v = __shfl_xor_sync(0xffffffffu, b0 ? x[0] : x[1], 1); if (b0) x[0] = v; else x[1] = v;
        v = __shfl_xor_sync(0xffffffffu, b0 ? x[2] : x[3], 1); if (b0) x[2] = v; else x[3] = v;
        v = __shfl_xor_sync(0xffffffffu, b1 ? x[0] : x[2], 2); if (b1) x[0] = v; else x[2] = v;
        v = __shfl_xor_sync(0xffffffffu, b1 ? x[1] : x[3], 2); if (b1) x[1] = v; else x[3] = v;
        d0[(u & 1) * 4 + (u >> 1) * 8 * 160] = make_uint4(x[0], x[1], x[2], x[3]);
      }
      if (hp == 1 && tid == 0) asm volatile("red.relaxed.gpu.global.add.u32 [%0], 1;" ::"l"(P.epoch + grp) : "memory");
    };
#pragma unroll 1
    for (int t = 0; t < 10; t++) {
      if (t < 8 && !(t & 1)) {
        oproj_chunk<true>(a, o0, o1, t, d0, d1, fullo0, w, tok & 3u, [&]() { prepare(t, true); });
        TSTAMP(10 + t);
        epilogue(t, true);
        t++;
      }
      if (t == 9 && finw) { finalize(); break; }
      oproj_chunk<false>(a, o0, o1, t, d0, d1, fullo0, w, tok & 3u, [&]() { prepare(t, false); });
      TSTAMP(10 + t);
      epilogue(t, false);
    }
    TSTAMP(9);
    __syncwarp();
    TDUMP();
  }
}

typedef CUresult (*EncodeFn)(CUtensorMap*, CUtensorMapDataType, cuuint32_t, void*, const cuuint64_t*, const cuuint64_t*,
                             const cuuint32_t*, const cuuint32_t*, CUtensorMapInterleave, CUtensorMapSwizzle,
                             CUtensorMapL2promotion, CUtensorMapFloatOOBfill);

static void encode(EncodeFn fn, CUtensorMap* m, const void* ptr, int rank, const cuuint64_t* dims, const cuuint64_t* strides,
                   const cuuint32_t* box) {
  cuuint32_t es[5] = {1, 1, 1, 1, 1};
  fn(m, CU_TENSOR_MAP_DATA_TYPE_BFLOAT16, (cuuint32_t)rank, const_cast<void*>(ptr), dims, strides, box, es,
     CU_TENSOR_MAP_INTERLEAVE_NONE, CU_TENSOR_MAP_SWIZZLE_128B, CU_TENSOR_MAP_L2_PROMOTION_L2_256B,
     CU_TENSOR_MAP_FLOAT_OOB_FILL_NONE);
}

}

extern "C" void kernel_launch(void* const* d_in, const int* in_sizes, int n_in, void* d_out, int out_size) {
  using namespace fk;
  static Params params;
  static const void* cached[10] = {nullptr};
  static EncodeFn fn = nullptr;
  if (!fn) {
    void* f = nullptr;
    cudaDriverEntryPointQueryResult st;
    cudaGetDriverEntryPoint("cuTensorMapEncodeTiled", &f, cudaEnableDefault, &st);
    fn = (EncodeFn)f;
    void* e = nullptr;
    cudaGetSymbolAddress(&e, g_epoch);
    params.epoch = (unsigned int*)e;
    cudaFuncSetAttribute(fused_kernel, cudaFuncAttributeMaxDynamicSharedMemorySize, SMEM_BYTES);
  }
  bool same = true;
  for (int i = 0; i < 10; i++) same = same && (cached[i] == d_in[i]);
  if (!same) {
    for (int p = 0; p < 2; p++) {
      const void* x = d_in[5 * p + 0];
      const void* k = d_in[5 * p + 1];
      const void* v = d_in[5 * p + 2];
      const void* wq = d_in[5 * p + 3];
      const void* wo = d_in[5 * p + 4];
      params.kp[p] = (const char*)k; params.vp[p] = (const char*)v;
      params.wqp[p] = (const char*)wq; params.xp[p] = (const char*)x; params.wop[p] = (const char*)wo;
      {
        cuuint64_t d[2] = {640, 768}, s[1] = {1280};
        cuuint32_t b[2] = {64, 96};
        encode(fn, &params.x[p], x, 2, d, s, b);
      }
      {
        cuuint64_t d[3] = {64, 640, 96}, s[2] = {12288, 128};
        cuuint32_t b[3] = {64, 64, 3};
        encode(fn, &params.wq[p], wq, 3, d, s, b);
      }
      {
        cuuint64_t d[4] = {192, 48, 32, 16}, s[3] = {384, 18432, 589824};
        cuuint32_t b[4] = {64, 48, 1, 4};
        encode(fn, &params.k[p], k, 4, d, s, b);
        encode(fn, &params.v[p], v, 4, d, s, b);
      }
      {
        cuuint64_t d[2] = {640, 6144}, s[1] = {1280};
        cuuint32_t b[2] = {64, 192};
        encode(fn, &params.wo[p], wo, 2, d, s, b);
      }
    }
    for (int i = 0; i < 10; i++) cached[i] = d_in[i];
  }
  fused_kernel<<<128, NTHREADS, SMEM_BYTES>>>(params, (__nv_bfloat16*)d_out);
}
```

```cpp
#include <cuda_runtime.h>
#include <cuda_bf16.h>
#include <cuda.h>
#include <stdint.h>

#define PF_ON 1
#define PF_WIN 4
#define PF_WIN1 4
#define PF_WIN0 3
#define FDELAY 500
#define FDELAY_C 1
#define NPRE 2
#define PAR 1
#define YB 1
#define GATHB 0
#define DEFER 0
#define PRE3 1
#define YFIRST 1
#define PACE 485
#define SMI 1
#define PACE2 PACE
#define PH2 1
#define PF_TRIG 3
#define PF0_FROM 5
#define PF_NW 2
#define PF0 1
#define QMMA 4
#define TOKEN_AT 8
#define TOKEN_S 8
#define WOPF 6
#define WOPF0 -2
#define WOPACE 485
#define STAG 1
#define TOK0 0x3eaabu
#define TOK1 0x57ffdu
#define TOK2 0xa555au
#define FIRSTW 2
#define SPIN_LIMIT (1u << 27)

namespace fk {

#define HEADMAP 0
constexpr int HM = HEADMAP ? 1 : 2, HS = HEADMAP ? 16 : 1;
constexpr int SLOT_BYTES = 24576;
constexpr int NSLOT = 9;
constexpr int XBUF_BYTES = 8192;
constexpr int XBUF_OFF = 8 * SLOT_BYTES;
constexpr int BAR_OFF = NSLOT * SLOT_BYTES;
constexpr int FULLO = 192, FULLE = 272, EMPTYE = 360;
constexpr int SINK_OFF = BAR_OFF + 1024;
constexpr int PF_DEPTH = 9;
constexpr int SMEM_BYTES = SINK_OFF + PF_DEPTH * 960 + 1024;
constexpr int NTHREADS = 512;

struct Params {
  CUtensorMap x[2], wq[2], k[2], v[2], wo[2];
  const char* kp[2]; const char* vp[2]; const char* wqp[2]; const char* xp[2]; const char* wop[2];
  unsigned int* epoch;
};

__device__ uint4 g_part[8 * 10 * 7 * (SLOT_BYTES / 16)];
__device__ unsigned int g_epoch[8];
#define TSTAMP(i)
#define PSTAMP(i)
#define HSTAMP(i)
#define GSTAMP(a, b)
#define HSTAMP2(i)
#define CSTAMP(i)
#define TDUMP()

#define XSTAMP(i)
#define ESTAMP(i) TSTAMP(i)
#define QSTAMP(i)
#define RSTAMP(i)
#define OSTAMP(i)
#define ZSTAMP(i) TSTAMP(i)
#define FSTAMP(i)
#define SNOW(v)
#define SPUT(i, v)
__device__ __forceinline__ uint32_t smem_u32(const void* p) { return (uint32_t)__cvta_generic_to_shared(p); }
__device__ __forceinline__ void mbar_init(uint32_t bar, uint32_t cnt) {
  asm volatile("mbarrier.init.shared::cta.b64 [%0], %1;" ::"r"(bar), "r"(cnt) : "memory");
}
__device__ __forceinline__ void mbar_expect_tx(uint32_t bar, uint32_t bytes) {
  asm volatile("mbarrier.arrive.expect_tx.shared::cta.b64 _, [%0], %1;" ::"r"(bar), "r"(bytes) : "memory");
}
__device__ __forceinline__ uint32_t mapa(uint32_t addr, uint32_t cta) {
  uint32_t r;
  asm volatile("mapa.shared::cluster.u32 %0, %1, %2;" : "=r"(r) : "r"(addr), "r"(cta));
  return r;
}
__device__ __forceinline__ void mbar_arrive_cluster(uint32_t remote_bar) {
  asm volatile("mbarrier.arrive.shared::cluster.b64 _, [%0];" ::"r"(remote_bar) : "memory");
}
__device__ __forceinline__ uint32_t mbar_try(uint32_t bar, uint32_t parity) {
  uint32_t ok;
  asm volatile("{\n.reg .pred p;\nmbarrier.try_wait.parity.shared::cta.b64 p, [%1], %2;\nselp.u32 %0, 1, 0, p;\n}\n"
               : "=r"(ok) : "r"(bar), "r"(parity) : "memory");
  return ok;
}
__device__ __forceinline__ uint32_t mbar_test(uint32_t bar, uint32_t parity) {
  uint32_t ok;
  asm volatile("{\n.reg .pred p;\nmbarrier.test_wait.parity.shared::cta.b64 p, [%1], %2;\nselp.u32 %0, 1, 0, p;\n}\n"
               : "=r"(ok) : "r"(bar), "r"(parity) : "memory");
  return ok;
}
__device__ __forceinline__ uint32_t mbar_try_cluster(uint32_t bar, uint32_t parity) {
  uint32_t ok;
  asm volatile("{\n.reg .pred p;\nmbarrier.try_wait.parity.acquire.cluster.shared::cta.b64 p, [%1], %2;\nselp.u32 %0, 1, 0, p;\n}\n"
               : "=r"(ok) : "r"(bar), "r"(parity) : "memory");
  return ok;
}
__device__ __forceinline__ uint32_t clk32() {
  uint32_t t;
  asm volatile("mov.u32 %0, %%clock;" : "=r"(t));
  return t;
}
#define DBGREC(a, b)
__device__ __forceinline__ void mbar_wait(uint32_t bar, uint32_t parity) {
  if (mbar_try(bar, parity)) return;
  const uint32_t t0 = clk32();
  while (!mbar_try(bar, parity)) {
    if (clk32() - t0 > SPIN_LIMIT) { DBGREC(bar, parity); break; }
  }
}
__device__ __forceinline__ void mbar_wait_cluster(uint32_t bar, uint32_t parity) {
  if (mbar_try_cluster(bar, parity)) return;
  const uint32_t t0 = clk32();
  while (!mbar_try_cluster(bar, parity)) {
    if (clk32() - t0 > SPIN_LIMIT) break;
  }
}
__device__ __forceinline__ void cluster_sync() {
  asm volatile("barrier.cluster.arrive.release.aligned;\nbarrier.cluster.wait.acquire.aligned;\n" ::: "memory");
}
__device__ __forceinline__ void tma2d(uint32_t dst, const CUtensorMap* m, int c0, int c1, uint32_t bar) {
  asm volatile("cp.async.bulk.tensor.2d.shared::cluster.global.mbarrier::complete_tx::bytes [%0], [%1, {%3, %4}], [%2];"
               ::"r"(dst), "l"(m), "r"(bar), "r"(c0), "r"(c1) : "memory");
}
__device__ __forceinline__ void tma2d_mc(uint32_t dst, const CUtensorMap* m, int c0, int c1, uint32_t bar, uint16_t mask) {
  asm volatile("cp.async.bulk.tensor.2d.shared::cluster.global.mbarrier::complete_tx::bytes.multicast::cluster [%0], [%1, {%3, %4}], [%2], %5;"
               ::"r"(dst), "l"(m), "r"(bar), "r"(c0), "r"(c1), "h"(mask) : "memory");
}
__device__ __forceinline__ void tma3d(uint32_t dst, const CUtensorMap* m, int c0, int c1, int c2, uint32_t bar) {
  asm volatile("cp.async.bulk.tensor.3d.shared::cluster.global.mbarrier::complete_tx::bytes [%0], [%1, {%3, %4, %5}], [%2];"
               ::"r"(dst), "l"(m), "r"(bar), "r"(c0), "r"(c1), "r"(c2) : "memory");
}
__device__ __forceinline__ void tma4d(uint32_t dst, const CUtensorMap* m, int c0, int c1, int c2, int c3, uint32_t bar) {
  asm volatile("cp.async.bulk.tensor.4d.shared::cluster.global.mbarrier::complete_tx::bytes [%0], [%1, {%3, %4, %5, %6}], [%2];"
               ::"r"(dst), "l"(m), "r"(bar), "r"(c0), "r"(c1), "r"(c2), "r"(c3) : "memory");
}
__device__ __forceinline__ void bulk_g2s(uint32_t dst, const void* src, uint32_t bytes, uint32_t bar) {
  asm volatile("cp.async.bulk.shared::cluster.global.mbarrier::complete_tx::bytes [%0], [%1], %2, [%3];"
               ::"r"(dst), "l"(src), "r"(bytes), "r"(bar) : "memory");
}
__device__ __forceinline__ void mbar_arrive(uint32_t bar) {
  asm volatile("mbarrier.arrive.shared::cta.b64 _, [%0];" ::"r"(bar) : "memory");
}
__device__ __forceinline__ uint32_t touch_l2(const void* p) {
  uint32_t v;
  asm volatile("ld.global.cg.L2::128B.b32 %0, [%1];" : "=r"(v) : "l"(p));
  return v;
}
__device__ __forceinline__ unsigned ld_acquire(const unsigned* p) {
  unsigned v;
  asm volatile("ld.acquire.gpu.global.u32 %0, [%1];" : "=r"(v) : "l"(p) : "memory");
  return v;
}
__device__ __forceinline__ void wg_fence() { asm volatile("wgmma.fence.sync.aligned;" ::: "memory"); }
__device__ __forceinline__ void wg_commit() { asm volatile("wgmma.commit_group.sync.aligned;" ::: "memory"); }
template <int N> __device__ __forceinline__ void wg_wait() { asm volatile("wgmma.wait_group.sync.aligned %0;" ::"n"(N) : "memory"); }
template <int N> __device__ __forceinline__ void fence_regs(float (&d)[N]) {
#pragma unroll
  for (int i = 0; i < N; i++) asm volatile("" : "+f"(d[i])::"memory");
}
template <int N> __device__ __forceinline__ void fence_regs(uint32_t (&d)[N]) {
#pragma unroll
  for (int i = 0; i < N; i++) asm volatile("" : "+r"(d[i])::"memory");
}
template <int N> __device__ __forceinline__ void pin_regs(const uint32_t* d, uint32_t never, uint32_t addr) {
#pragma unroll
  for (int i = 0; i < N; i += 4)
    asm volatile("{\n.reg .pred p;\nsetp.ne.u32 p, %5, 0;\n@p st.shared.v4.b32 [%0], {%1, %2, %3, %4};\n}\n"
                 ::"r"(addr), "r"(d[i]), "r"(d[i + 1]), "r"(d[i + 2]), "r"(d[i + 3]), "r"(never) : "memory");
}
__device__ __forceinline__ uint32_t pack_bf16(float lo, float hi) {
  uint32_t r;
  asm("cvt.rn.bf16x2.f32 %0, %1, %2;" : "=r"(r) : "f"(hi), "f"(lo));
  return r;
}
__device__ __forceinline__ float ex2(float x) {
  float r;
  asm("ex2.approx.ftz.f32 %0, %1;" : "=f"(r) : "f"(x));
  return r;
}
__device__ __forceinline__ float rcp(float x) {
  float r;
  asm("rcp.approx.ftz.f32 %0, %1;" : "=f"(r) : "f"(x));
  return r;
}
__device__ __forceinline__ uint64_t make_desc(uint32_t addr, uint32_t lbo, uint32_t sbo) {
  return (uint64_t)((addr & 0x3FFFFu) >> 4) | ((uint64_t)(lbo >> 4) << 16) | ((uint64_t)(sbo >> 4) << 32) | (1ull << 62);
}

__device__ __forceinline__ void wgmma_n192_ss_tb(float (&d)[96], uint64_t da, uint64_t db, int scale_d) {
  asm volatile("{\n.reg .pred p;\nsetp.ne.b32 p, %98, 0;\n"
    "wgmma.mma_async.sync.aligned.m64n192k16.f32.bf16.bf16 "
    "{%0, %1, %2, %3, %4, %5, %6, %7, %8, %9, %10, %11, %12, %13, %14, %15, %16, %17, %18, %19, %20, %21, %22, %23, %24, %25, %26, %27, %28, %29, %30, %31, %32, %33, %34, %35, %36, %37, %38, %39, %40, %41, %42, %43, %44, %45, %46, %47, %48, %49, %50, %51, %52, %53, %54, %55, %56, %57, %58, %59, %60, %61, %62, %63, %64, %65, %66, %67, %68, %69, %70, %71, %72, %73, %74, %75, %76, %77, %78, %79, %80, %81, %82, %83, %84, %85, %86, %87, %88, %89, %90, %91, %92, %93, %94, %95}, "
    "%96, %97, p, 1, 1, 0, 1;\n}\n"
    : "+f"(d[0]), "+f"(d[1]), "+f"(d[2]), "+f"(d[3]), "+f"(d[4]), "+f"(d[5]), "+f"(d[6]), "+f"(d[7]), "+f"(d[8]), "+f"(d[9]), "+f"(d[10]), "+f"(d[11]), "+f"(d[12]), "+f"(d[13]), "+f"(d[14]), "+f"(d[15]), "+f"(d[16]), "+f"(d[17]), "+f"(d[18]), "+f"(d[19]), "+f"(d[20]), "+f"(d[21]), "+f"(d[22]), "+f"(d[23]), "+f"(d[24]), "+f"(d[25]), "+f"(d[26]), "+f"(d[27]), "+f"(d[28]), "+f"(d[29]), "+f"(d[30]), "+f"(d[31]), "+f"(d[32]), "+f"(d[33]), "+f"(d[34]), "+f"(d[35]), "+f"(d[36]), "+f"(d[37]), "+f"(d[38]), "+f"(d[39]), "+f"(d[40]), "+f"(d[41]), "+f"(d[42]), "+f"(d[43]), "+f"(d[44]), "+f"(d[45]), "+f"(d[46]), "+f"(d[47]), "+f"(d[48]), "+f"(d[49]), "+f"(d[50]), "+f"(d[51]), "+f"(d[52]), "+f"(d[53]), "+f"(d[54]), "+f"(d[55]), "+f"(d[56]), "+f"(d[57]), "+f"(d[58]), "+f"(d[59]), "+f"(d[60]), "+f"(d[61]), "+f"(d[62]), "+f"(d[63]), "+f"(d[64]), "+f"(d[65]), "+f"(d[66]), "+f"(d[67]), "+f"(d[68]), "+f"(d[69]), "+f"(d[70]), "+f"(d[71]), "+f"(d[72]), "+f"(d[73]), "+f"(d[74]), "+f"(d[75]), "+f"(d[76]), "+f"(d[77]), "+f"(d[78]), "+f"(d[79]), "+f"(d[80]), "+f"(d[81]), "+f"(d[82]), "+f"(d[83]), "+f"(d[84]), "+f"(d[85]), "+f"(d[86]), "+f"(d[87]), "+f"(d[88]), "+f"(d[89]), "+f"(d[90]), "+f"(d[91]), "+f"(d[92]), "+f"(d[93]), "+f"(d[94]), "+f"(d[95])
    : "l"(da), "l"(db), "r"(scale_d));
}
__device__ __forceinline__ void wgmma_n96_rs(float (&d)[48], uint32_t a0, uint32_t a1, uint32_t a2, uint32_t a3, uint64_t db, int scale_d) {
  asm volatile("{\n.reg .pred p;\nsetp.ne.b32 p, %53, 0;\n"
    "wgmma.mma_async.sync.aligned.m64n96k16.f32.bf16.bf16 "
    "{%0, %1, %2, %3, %4, %5, %6, %7, %8, %9, %10, %11, %12, %13, %14, %15, %16, %17, %18, %19, %20, %21, %22, %23, %24, %25, %26, %27, %28, %29, %30, %31, %32, %33, %34, %35, %36, %37, %38, %39, %40, %41, %42, %43, %44, %45, %46, %47}, "
    "{%48, %49, %50, %51}, %52, p, 1, 1, 0;\n}\n"
    : "+f"(d[0]), "+f"(d[1]), "+f"(d[2]), "+f"(d[3]), "+f"(d[4]), "+f"(d[5]), "+f"(d[6]), "+f"(d[7]), "+f"(d[8]), "+f"(d[9]), "+f"(d[10]), "+f"(d[11]), "+f"(d[12]), "+f"(d[13]), "+f"(d[14]), "+f"(d[15]), "+f"(d[16]), "+f"(d[17]), "+f"(d[18]), "+f"(d[19]), "+f"(d[20]), "+f"(d[21]), "+f"(d[22]), "+f"(d[23]), "+f"(d[24]), "+f"(d[25]), "+f"(d[26]), "+f"(d[27]), "+f"(d[28]), "+f"(d[29]), "+f"(d[30]), "+f"(d[31]), "+f"(d[32]), "+f"(d[33]), "+f"(d[34]), "+f"(d[35]), "+f"(d[36]), "+f"(d[37]), "+f"(d[38]), "+f"(d[39]), "+f"(d[40]), "+f"(d[41]), "+f"(d[42]), "+f"(d[43]), "+f"(d[44]), "+f"(d[45]), "+f"(d[46]), "+f"(d[47])
    : "r"(a0), "r"(a1), "r"(a2), "r"(a3), "l"(db), "r"(scale_d));
}
__device__ __forceinline__ void wgmma_n64_rs_tb(float (&d)[32], uint32_t a0, uint32_t a1, uint32_t a2, uint32_t a3, uint64_t db, int scale_d) {
  asm volatile("{\n.reg .pred p;\nsetp.ne.b32 p, %37, 0;\n"
    "wgmma.mma_async.sync.aligned.m64n64k16.f32.bf16.bf16 "
    "{%0, %1, %2, %3, %4, %5, %6, %7, %8, %9, %10, %11, %12, %13, %14, %15, %16, %17, %18, %19, %20, %21, %22, %23, %24, %25, %26, %27, %28, %29, %30, %31}, "
    "{%32, %33, %34, %35}, %36, p, 1, 1, 1;\n}\n"
    : "+f"(d[0]), "+f"(d[1]), "+f"(d[2]), "+f"(d[3]), "+f"(d[4]), "+f"(d[5]), "+f"(d[6]), "+f"(d[7]), "+f"(d[8]), "+f"(d[9]), "+f"(d[10]), "+f"(d[11]), "+f"(d[12]), "+f"(d[13]), "+f"(d[14]), "+f"(d[15]), "+f"(d[16]), "+f"(d[17]), "+f"(d[18]), "+f"(d[19]), "+f"(d[20]), "+f"(d[21]), "+f"(d[22]), "+f"(d[23]), "+f"(d[24]), "+f"(d[25]), "+f"(d[26]), "+f"(d[27]), "+f"(d[28]), "+f"(d[29]), "+f"(d[30]), "+f"(d[31])
    : "r"(a0), "r"(a1), "r"(a2), "r"(a3), "l"(db), "r"(scale_d));
}

__device__ __forceinline__ int chunk_of(int i, int off) { const int c = i + off; return c >= 10 ? c - 10 : c; }
__device__ __forceinline__ int pos_of(int i, int c) { return i - (i > chunk_of(c, 6)) - (i > chunk_of(c, 1)); }
#define SKEW 1
#define RSPLIT 0
__device__ __forceinline__ int index_at(int t, int r, bool both) {
  if (r == 0) return (t < 8 || both) ? (t ^ 1) : t;
  return (SKEW && !both && (t == 7 || t == 8)) ? 15 - t : t;
}

constexpr int KPOS = 43;
__device__ __forceinline__ void do_item(const Params& P, int i, int p, int tg, int h0, int r, uint32_t dst, uint32_t bar) {
  if (i >= 46) {
    const int h1 = i >= 49;
    tma4d(dst, &P.v[p], (i - 46 - 3 * h1) * 64, 0, h0 + HS * h1, tg * 4, bar);
  } else if (i >= KPOS && i < KPOS + 3) {
    tma4d(dst, &P.k[p], (i - KPOS) * 64, 0, h0 + HS, tg * 4, bar);
  } else if (i >= 20 && i < 23) {
    tma4d(dst, &P.k[p], (i - 20) * 64, 0, h0, tg * 4, bar);
  } else {
    const int hh = i >= 23;
    const int j = i - 23 * hh - 3 * (i >= KPOS);
    const int kc = j >> 1;
    if (!(j & 1)) tma2d_mc(dst + r * 12288, &P.x[p], kc * 64, tg * 192 + r * 96, bar, (uint16_t)3);
    else tma3d(dst, &P.wq[p], 0, kc * 64, (h0 + HS * hh) * 3, bar);
  }
}

struct Ring {
  uint32_t slot, phase;
  __device__ __forceinline__ void advance() {
    if (++slot == NSLOT) { slot = 0; phase ^= 1; }
  }
};

__device__ __forceinline__ void load_tile(uint32_t (&x)[16], uint32_t addr) {
#pragma unroll
  for (int j = 0; j < 4; j++)
    asm volatile("ld.shared.v4.b32 {%0, %1, %2, %3}, [%4];"
                 : "=r"(x[4 * j]), "=r"(x[4 * j + 1]), "=r"(x[4 * j + 2]), "=r"(x[4 * j + 3]) : "r"(addr + j * 2048) : "memory");
}
__device__ __forceinline__ void store_tile(uint32_t addr, const float (&a)[32]) {
#pragma unroll
  for (int j = 0; j < 4; j++)
    asm volatile("st.shared.v4.b32 [%0], {%1, %2, %3, %4};"
                 ::"r"(addr + j * 2048), "r"(pack_bf16(a[8 * j], a[8 * j + 1])), "r"(pack_bf16(a[8 * j + 2], a[8 * j + 3])),
                   "r"(pack_bf16(a[8 * j + 4], a[8 * j + 5])), "r"(pack_bf16(a[8 * j + 6], a[8 * j + 7])) : "memory");
}
__device__ __forceinline__ uint32_t add_bf16x2(uint32_t a, uint32_t b) {
  uint32_t r;
  asm("add.rn.bf16x2 %0, %1, %2;" : "=r"(r) : "r"(a), "r"(b));
  return r;
}
template <int LUT> __device__ __forceinline__ uint32_t lop3(uint32_t a, uint32_t b, uint32_t c) {
  uint32_t r;
  asm("lop3.b32 %0, %1, %2, %3, %4;" : "=r"(r) : "r"(a), "r"(b), "r"(c), "n"(LUT));
  return r;
}
__device__ __forceinline__ uint32_t tile_ok(const uint32_t (&y)[16], uint32_t tm) {
  return (y[0] ^ tm) & (y[4] ^ tm) & (y[8] ^ tm) & (y[12] ^ tm) & 1u;
}
__device__ __forceinline__ void add_tile(float (&a)[32], const uint32_t (&x)[16]) {
#pragma unroll
  for (int j = 0; j < 16; j++) {
    a[2 * j] += __uint_as_float(x[j] << 16);
    a[2 * j + 1] += __uint_as_float(x[j] & 0xffff0000u);
  }
}
constexpr uint64_t OSLOTS = 0x83d65683d6541d9ull;
__device__ __forceinline__ uint32_t oslot(uint32_t j) { return (uint32_t)(OSLOTS >> (3 * j)) & 7u; }

constexpr float SM_SCALE = 0.07216878364870322f * 1.4426950408889634f;
struct Front {
  Ring rg;
  uint32_t sbase, full0, rel0, never;
  int w, lane, hf;
  __device__ __forceinline__ uint32_t tsb() const { return full0 + 512 + w * 128; }
  __device__ __forceinline__ void release(uint32_t s) const { if (lane < 2) mbar_arrive_cluster(rel0 + 8 * s); }
  __device__ __forceinline__ uint32_t next() {
    const uint32_t s = rg.slot;
    mbar_wait(full0 + 8 * s, rg.phase);
    rg.advance();
    return s;
  }
  template <bool FIRST> __device__ __forceinline__ void qchunk(float (&acc)[96], uint32_t& sx, uint32_t& sw) {
    sx = next(); sw = next();
    const uint64_t da = make_desc(sbase + sx * SLOT_BYTES + w * 8192, 16, 1024);
    const uint64_t db = make_desc(sbase + sw * SLOT_BYTES, 8192, 1024);
    wg_fence();
#pragma unroll
    for (int s = 0; s < QMMA; s++) wgmma_n192_ss_tb(acc, da + 2 * s, db + 128 * s, !FIRST || s != 0);
    wg_commit();
  }
  __device__ __forceinline__ void qrest(float (&acc)[96], uint32_t (&qf)[48], uint32_t psx, uint32_t psw, int kc0, int tbase) {
#pragma unroll 1
    for (int kc = kc0; kc < 10; kc++) {
      uint32_t sx, sw;
      qchunk<false>(acc, sx, sw);
      QSTAMP(20 + kc);
      wg_wait<1>(); release(psx); release(psw);
      psx = sx; psw = sw;
    }
    wg_wait<0>();
    fence_regs(acc);
    release(psx); release(psw);
#pragma unroll
    for (int i = 24; i < 48; i++) qf[i] = pack_bf16(acc[2 * i], acc[2 * i + 1]);
    pin_regs<24>(qf + 24, never, full0);
#pragma unroll
    for (int i = 0; i < 24; i++) qf[i] = pack_bf16(acc[2 * i], acc[2 * i + 1]);
    pin_regs<24>(qf, never, full0);
    fence_regs(qf);
  }
  __device__ __forceinline__ void scores(float (&v)[24], const uint32_t (&qf)[48]) {
    float sacc[48];
    uint32_t ks[3];
#pragma unroll
    for (int dc = 0; dc < 3; dc++) {
      ks[dc] = next();
      const uint64_t db = make_desc(sbase + ks[dc] * SLOT_BYTES + w * 6144, 16, 1024);
      wg_fence();
#pragma unroll
      for (int s = 0; s < 4; s++) {
        const int j = dc * 4 + s;
        wgmma_n96_rs(sacc, qf[4 * j], qf[4 * j + 1], qf[4 * j + 2], qf[4 * j + 3], db + 2 * s, j != 0);
      }
    }
    wg_commit();
    wg_wait<0>();
    fence_regs(sacc);
    release(ks[0]); release(ks[1]); release(ks[2]);
#pragma unroll
    for (int i = 0; i < 24; i++) v[i] = hf ? sacc[24 + i] : sacc[i];
    fence_regs(v);
  }
  __device__ __forceinline__ void sm_max(const float (&v)[24], float& b0, float& b1) {
    float m0 = v[0], m1 = v[2];
#pragma unroll
    for (int t = 0; t < 6; t++) {
      m0 = fmaxf(m0, fmaxf(v[4 * t], v[4 * t + 1]));
      m1 = fmaxf(m1, fmaxf(v[4 * t + 2], v[4 * t + 3]));
    }
    m0 = fmaxf(m0, __shfl_xor_sync(0xffffffffu, m0, 1));
    m1 = fmaxf(m1, __shfl_xor_sync(0xffffffffu, m1, 1));
    m0 = fmaxf(m0, __shfl_xor_sync(0xffffffffu, m0, 2));
    m1 = fmaxf(m1, __shfl_xor_sync(0xffffffffu, m1, 2));
    b0 = m0 * SM_SCALE; b1 = m1 * SM_SCALE;
  }
  __device__ __forceinline__ void sm_exp(float (&v)[24], float& b0, float& b1) {
    float s0 = 0.f, s1 = 0.f;
#pragma unroll
    for (int t = 0; t < 6; t++) {
      v[4 * t] = ex2(fmaf(v[4 * t], SM_SCALE, -b0));
      v[4 * t + 1] = ex2(fmaf(v[4 * t + 1], SM_SCALE, -b0));
      v[4 * t + 2] = ex2(fmaf(v[4 * t + 2], SM_SCALE, -b1));
      v[4 * t + 3] = ex2(fmaf(v[4 * t + 3], SM_SCALE, -b1));
      s0 += v[4 * t] + v[4 * t + 1];
      s1 += v[4 * t + 2] + v[4 * t + 3];
    }
    s0 += __shfl_xor_sync(0xffffffffu, s0, 1);
    s1 += __shfl_xor_sync(0xffffffffu, s1, 1);
    s0 += __shfl_xor_sync(0xffffffffu, s0, 2);
    s1 += __shfl_xor_sync(0xffffffffu, s1, 2);
    b0 = rcp(s0); b1 = rcp(s1);
  }
  __device__ __forceinline__ void sm_pack(uint32_t (&pk)[12], const float (&v)[24], float r0, float r1) {
#pragma unroll
    for (int t = 0; t < 6; t++) {
      pk[2 * t] = pack_bf16(v[4 * t] * r0, v[4 * t + 1] * r0);
      pk[2 * t + 1] = pack_bf16(v[4 * t + 2] * r1, v[4 * t + 3] * r1);
    }
    pin_regs<12>(pk, never, full0);
    fence_regs(pk);
  }
  __device__ __forceinline__ void softmax(uint32_t (&pk)[12], float (&v)[24]) {
    float b0, b1;
    sm_max(v, b0, b1);
    sm_exp(v, b0, b1);
    sm_pack(pk, v, b0, b1);
  }
  __device__ __forceinline__ void expand(uint32_t (&pa)[24], uint32_t (&pk)[12]) {
    fence_regs(pk);
#pragma unroll
    for (int i = 0; i < 12; i++) {
      pa[i] = hf ? 0u : pk[i];
      pa[12 + i] = hf ? pk[i] : 0u;
    }
    fence_regs(pa);
  }
  __device__ __forceinline__ void pv(float (&oa)[32], const uint32_t (&pa)[24], int s, int parity) {
    mbar_wait(full0 + 8 * s, parity);
    const uint64_t db = make_desc(sbase + s * SLOT_BYTES + w * 6144, 16, 1024);
    wg_fence();
#pragma unroll
    for (int j = 0; j < 6; j++) wgmma_n64_rs_tb(oa, pa[4 * j], pa[4 * j + 1], pa[4 * j + 2], pa[4 * j + 3], db + 128 * j, j != 0);
  }
  __device__ __forceinline__ void pack16(uint32_t* o, const float (&oa)[32]) {
#pragma unroll
    for (int i = 0; i < 16; i++) o[i] = pack_bf16(oa[2 * i], oa[2 * i + 1]);
    pin_regs<16>(o, never, full0);
  }
  __device__ __forceinline__ void early(float (&a)[32], const uint32_t (&o0)[48], int t) {
    mbar_wait(full0 + FULLE + 8 * t, 0);
    const uint64_t db = make_desc(sbase + (4 + t) * SLOT_BYTES, 16, 1024);
    wg_fence();
#pragma unroll
    for (int j = 0; j < 12; j++)
      wgmma_n64_rs_tb(a, o0[4 * j], o0[4 * j + 1], o0[4 * j + 2], o0[4 * j + 3], db + 128 * j, j != 0);
    wg_commit();
  }
  __device__ __forceinline__ void park(float (&a)[32], int t) {
    fence_regs(a);
    if (lane == 0) mbar_arrive(full0 + EMPTYE + 8 * (t + 1));
    mbar_wait(full0 + EMPTYE + 8 * t, 0);
    uint32_t tid;
    asm volatile("mov.u32 %0, %%tid.x;" : "=r"(tid));
    store_tile(sbase + oslot(4 * t) * SLOT_BYTES + (tid >> 7) * XBUF_BYTES + (tid & 127) * 16, a);
  }
  __device__ __forceinline__ void run(uint32_t (&o0)[48], uint32_t (&o1)[48]) {
    uint32_t pk[12], pa[24];
    float v[24];
    {
      uint32_t qf[48];
      {
        float acc[96];
        uint32_t sx, sw;
        qchunk<true>(acc, sx, sw);
        { const int tbase = 1; (void)tbase; QSTAMP(20); }
        qrest(acc, qf, sx, sw, 1, 1);
      }
      TSTAMP(1);
      scores(v, qf);
      TSTAMP(2);
    }
    {
      uint32_t qf[48];
      {
        float acc[96];
        uint32_t ax, aw, bx, bw;
        qchunk<true>(acc, ax, aw);
        qchunk<false>(acc, bx, bw);
        softmax(pk, v);
        TSTAMP(3);
        wg_wait<1>(); release(ax); release(aw);
        qrest(acc, qf, bx, bw, 2, 4);
      }
      TSTAMP(4);
      scores(v, qf);
      TSTAMP(5);
    }
    {
      float oa[32], ob[32], oc[32];
      expand(pa, pk);
      float b0, b1;
      pv(oa, pa, 1, 1);
      sm_max(v, b0, b1);
      asm volatile("" : "+f"(b0), "+f"(b1));
      pv(ob, pa, 2, 1);
      sm_exp(v, b0, b1);
      fence_regs(v);
      asm volatile("" : "+f"(b0), "+f"(b1));
      pv(oc, pa, 3, 1);
      wg_commit();
      XSTAMP(20);
      sm_pack(pk, v, b0, b1);
      XSTAMP(21);
      wg_wait<0>();
      fence_regs(oa); fence_regs(ob); fence_regs(oc);
      XSTAMP(22);
      release(2); release(3);
      if (lane == 0) mbar_arrive(full0 + EMPTYE);
      pack16(o0, oa); pack16(o0 + 16, ob); pack16(o0 + 32, oc);
      fence_regs(o0);
    }
    {
      float oa[32], ob[32];
      early(oa, o0, 0);
      early(ob, o0, 1);
      XSTAMP(23);
      wg_wait<1>(); park(oa, 0);
      early(oa, o0, 2);
      wg_wait<1>(); park(ob, 1);
      early(ob, o0, 3);
      XSTAMP(24);
      wg_wait<1>(); park(oa, 2);
      wg_wait<0>(); park(ob, 3);
      XSTAMP(25);
      fence_regs(o0);
#pragma unroll
      for (int i = 0; i < 12; i++) o0[i] += never;
      fence_regs(o0);
      expand(pa, pk);
      pv(oa, pa, 8, 1);
      pv(ob, pa, 0, 0);
      wg_commit();
      XSTAMP(26);
      wg_wait<0>();
      fence_regs(oa); fence_regs(ob);
      XSTAMP(27);
      release(8); release(0);
      pack16(o1, oa); pack16(o1 + 16, ob);
      float oc[32];
      pv(oc, pa, 2, 0);
      wg_commit();
      XSTAMP(28);
      wg_wait<0>();
      fence_regs(oc);
      release(2);
      pack16(o1 + 32, oc);
    }
    TSTAMP(6);
  }
};

__device__ __forceinline__ uint32_t oslot_addr(uint32_t sbase, uint32_t j) { return sbase + oslot(j) * SLOT_BYTES; }
template <bool EARLY, class Mid>
__device__ __forceinline__ void oproj_chunk(float (&a)[32], const uint32_t (&o0)[48], const uint32_t (&o1)[48], int t,
                                            uint32_t d0, uint32_t d1, uint32_t fullo0, int w, uint32_t nxt, Mid mid) {
  auto tsb = [&]() { return fullo0 - FULLO + 512 + w * 128; };
  (void)tsb;
  OSTAMP(0);
  mbar_wait(fullo0 + 8 * t, 0);
  OSTAMP(1);
  if (!EARLY || t != 0 || w != FIRSTW) asm volatile("bar.sync %0, 256;" ::"r"(1 + w) : "memory");
  OSTAMP(2);
  wg_fence();
  if (!EARLY) {
    const uint64_t db = d0 | (0x40000040ull << 32);
#pragma unroll
    for (int j = 0; j < 12; j++)
      wgmma_n64_rs_tb(a, o0[4 * j], o0[4 * j + 1], o0[4 * j + 2], o0[4 * j + 3], db + 128 * j, j != 0);
  }
  {
    const uint64_t db = d1 | (0x40000040ull << 32);
#pragma unroll
    for (int j = 0; j < 12; j++) {
      wgmma_n64_rs_tb(a, o1[4 * j], o1[4 * j + 1], o1[4 * j + 2], o1[4 * j + 3], db + 128 * j, !EARLY || j != 0);
      if (j == (EARLY ? TOKEN_S : TOKEN_AT) && (EARLY || nxt)) asm volatile("bar.arrive %0, 256;" ::"r"(nxt) : "memory");
    }
    wg_commit();
  }
  OSTAMP(3);
  mid();
  OSTAMP(4);
  wg_wait<0>();
  fence_regs(a);
}

__global__ void __cluster_dims__(2, 1, 1) __launch_bounds__(NTHREADS, 1)
fused_kernel(const __grid_constant__ Params P, __nv_bfloat16* __restrict__ out) {
  extern __shared__ uint8_t smem_raw[];
  const uint32_t sbase = (smem_u32(smem_raw) + 1023u) & ~1023u;
  const uint32_t full0 = sbase + BAR_OFF;
  const uint32_t empty0 = full0 + 72;
  const uint32_t xfull0 = full0 + 144;
  const uint32_t xempty0 = full0 + 168;
  const uint32_t fullo0 = full0 + FULLO;
  const uint32_t emptyo0 = full0 + 400;
  const uint32_t eready = full0 + 344;
  const uint32_t epoch_s = full0 + 352;
  const uint32_t dtab = full0 + 480;
  const uint32_t emptye0 = full0 + EMPTYE;

  const int tid = threadIdx.x, lane = tid & 31;
  const int warp = __shfl_sync(0xffffffffu, tid >> 5, 0);
  auto tsb = [&]() { return full0 + 512 + (warp >> 2) * 128; };
  const int bid = blockIdx.x;
  const int hp = bid & 15, tg = (bid >> 4) & 3, p = bid >> 6;
  const int r = hp & 1;
  const int h0 = hp * HM;
  const int grp = p * 4 + tg;
  const int off = (hp >> 1) + (hp >> 3);
  const bool both = off == 0 || off == 5;
  const bool fin = r == 1 || both;

  if (warp >= 12) {
    asm volatile("setmaxnreg.dec.sync.aligned.u32 32;");
    if (tid == 384) {
#pragma unroll
      for (int i = 2; i < NSLOT; i++) mbar_init(full0 + 8 * i, 1);
      asm volatile("fence.mbarrier_init.release.cluster;" ::: "memory");
    }
    __syncwarp();
    asm volatile("barrier.cluster.arrive.relaxed.aligned;" ::: "memory");
    if (warp == 12) {
      SNOW(sa_);
      if (lane == 0) {
#pragma unroll 1
        for (int c = 1; c < 5; c++) {
          if (c == FDELAY_C) { const uint32_t t0 = clk32(); while (clk32() - t0 < FDELAY) {} }
          mbar_expect_tx(full0 + 16 * c, SLOT_BYTES);
          tma2d(sbase + 2 * c * SLOT_BYTES, &P.x[p], c * 64, tg * 192, full0 + 16 * c);
          tma2d(sbase + 2 * c * SLOT_BYTES + 12288, &P.x[p], c * 64, tg * 192 + 96, full0 + 16 * c);
          if (c == 4) break;
          mbar_expect_tx(full0 + 8 + 16 * c, SLOT_BYTES);
          tma3d(sbase + (2 * c + 1) * SLOT_BYTES, &P.wq[p], 0, c * 64, h0 * 3, full0 + 8 + 16 * c);
        }
        asm volatile("prefetch.tensormap [%0];" ::"l"(&P.k[p]) : "memory");
        asm volatile("prefetch.tensormap [%0];" ::"l"(&P.v[p]) : "memory");
        asm volatile("prefetch.tensormap [%0];" ::"l"(&P.wo[p]) : "memory");
      }
      SNOW(sb_);
      __syncwarp();
      asm volatile("barrier.cluster.wait.aligned;" ::: "memory");
      if (lane == 0) {
        TSTAMP(3); CSTAMP(28);
        uint32_t slot = 0, phase = 1;
#pragma unroll 1
        for (int i = NSLOT; i < 49; i++) {
          mbar_wait(empty0 + 8 * slot, phase ^ 1);
          mbar_expect_tx(full0 + 8 * slot, SLOT_BYTES);
          do_item(P, i, p, tg, h0, r, sbase + slot * SLOT_BYTES, full0 + 8 * slot);
          if (++slot == NSLOT) { slot = 0; phase ^= 1; }
        }
        TSTAMP(2); CSTAMP(29);
#pragma unroll 1
        for (int e = 0; e < 23; e++) {
          int j;
          uint32_t bar;
          if (e < 11) {
            slot = (uint32_t)(0x20732087654ull >> (4 * e)) & 15u;
            if (e == 8) mbar_wait(emptye0 + 32, 0);
            else mbar_wait(empty0 + 8 * slot, e >= 5 && e < 8);
            if (e >= 4 && e < 7) {
              mbar_expect_tx(full0 + 8 * slot, SLOT_BYTES);
              do_item(P, 45 + e, p, tg, h0, r, sbase + slot * SLOT_BYTES, full0 + 8 * slot);
              continue;
            }
            j = e < 4 ? 4 * e : e - 6 + (e == 10);
          } else {
            const int n = e - 11;
            slot = oslot(n);
            mbar_wait(emptyo0 + 8 * (n >> 1), 0);
            asm volatile("fence.proxy.async.shared::cta;" ::: "memory");
            j = n + 6 + (n >= 2) + (n >= 5);
          }
          bar = e < 4 ? full0 + FULLE + 8 * e : fullo0 + 8 * (j >> 1);
          mbar_expect_tx(bar, SLOT_BYTES);
          tma2d(sbase + slot * SLOT_BYTES, &P.wo[p], chunk_of(index_at(j >> 1, r, both), off) * 64, (h0 + HS * (j & 1)) * 192, bar);
        }
        TSTAMP(1); CSTAMP(30);
        if (fin || RSPLIT) {
          const int lo = RSPLIT && !fin ? 2 * XBUF_BYTES : 0, hi = RSPLIT && !both && r ? 2 * XBUF_BYTES : 3 * XBUF_BYTES;
          const char* src = reinterpret_cast<const char*>(g_part) + (size_t)(grp * 10 + chunk_of(both ? 8 + r : 9, off)) * 7 * SLOT_BYTES;
          mbar_wait(emptyo0 + 8 * 6, 0);
          asm volatile("fence.proxy.async.shared::cta;" ::: "memory");
          mbar_expect_tx(fullo0 + 8 * 14, 2 * (hi - lo));
          TSTAMP(4);
          bulk_g2s(oslot_addr(sbase, 12) + lo, src + lo, hi - lo, fullo0 + 8 * 14);
          bulk_g2s(oslot_addr(sbase, 13) + lo, src + SLOT_BYTES + lo, hi - lo, fullo0 + 8 * 14);
          TSTAMP(5);
          mbar_wait(emptyo0 + 8 * 7, 0);
          asm volatile("fence.proxy.async.shared::cta;" ::: "memory");
          TSTAMP(6);
#pragma unroll 1
          for (int u = hi - XBUF_BYTES; u >= lo; u -= XBUF_BYTES) {
            const uint32_t bar = fullo0 + 8 * 16 + (u >> 10);
            mbar_expect_tx(bar, 2 * XBUF_BYTES);
            bulk_g2s(oslot_addr(sbase, 14) + u, src + 2 * SLOT_BYTES + u, XBUF_BYTES, bar);
            bulk_g2s(oslot_addr(sbase, 15) + u, src + 3 * SLOT_BYTES + u, XBUF_BYTES, bar);
          }
          TSTAMP(7);
        }
      }
    } else {
      const int w = warp - 13;
      unsigned epoch;
      asm volatile("ld.global.cg.u32 %0, [%1];" : "=r"(epoch) : "l"(P.epoch + grp));
      {
        uint32_t sink = sbase + SINK_OFF + (w * 20 + lane) * 16;
        int un = 0;
        uint32_t rot = 0;
        asm volatile("barrier.cluster.wait.aligned;" ::: "memory");
        mbar_wait(full0 + 8 * PF_TRIG, 0);
        uint32_t due = clk32();
#pragma unroll 1
        for (int ph = PF0 ? -1 : 0; ph < 5; ph++) {
          const char* q;
          int nb = 4, nt = 3, nl = 16;
          uint32_t sb = 589824;
          if (ph == 1 || ph < 0) {
            q = P.wqp[p] + (size_t)(lane * 4 + tg) * 12288 + (h0 + HS * (ph > 0)) * 384 + w * 128;
            nb = 10; nt = 1; sb = 786432;
            if (ph < 0) {
              nl = 20;
              if (lane >= 16) { q = P.xp[p] + (size_t)(tg * 192 + hp * 12 + w * 4 + lane - 16) * 1280; sb = 128; }
              nb = 10 - PF0_FROM; q += PF0_FROM * sb;
            }
          } else {
            q = (ph < 3 ? P.kp[p] : P.vp[p]) + (size_t)(tg * 128 + h0 + HS * (ph == 2 || ph == 4)) * 18432 + (w * 16 + lane) * 128;
          }
#pragma unroll 1
          for (int b = 0; b < nb; b++, q += sb) {
            if (ph > 0 && mbar_test(emptye0 + 32, 0)) break;
#pragma unroll 1
            for (int t = 0; t < nt; t++) {
              if (ph < 0) asm volatile("cp.async.wait_group %0;" ::"n"(PF_WIN0 - 1) : "memory");
              else if (ph < PF_NW) asm volatile("cp.async.wait_group %0;" ::"n"(PF_WIN1 - 1) : "memory");
              else asm volatile("cp.async.wait_group %0;" ::"n"(PF_WIN - 1) : "memory");
              if (PACE) {
                while ((int)(clk32() - due) < 0) __nanosleep(32);
                due += ph >= PH2 ? PACE2 : PACE;
              }
              if (!(un & 1)) { PSTAMP(un >> 1); }
              if (lane < nl)
                asm volatile("cp.async.cg.shared.global.L2::128B [%0], [%1], 16;" ::"r"(sink + rot), "l"(q + t * 6144) : "memory");
              asm volatile("cp.async.commit_group;" ::: "memory");
              un++;
              rot = rot == (PF_DEPTH - 1) * 960 ? 0 : rot + 960;
            }
          }
          if (ph == 0) {
            if (lane < 5) {
              const int ci = 2 * lane + r, c = chunk_of(ci, off);
              asm volatile("st.shared.u32 [%0], %1;" ::"r"(dtab + 4 * lane), "r"(((grp * 10 + c) * 7 + pos_of(ci, c)) * SLOT_BYTES) : "memory");
            }
            __syncwarp();
            if (lane == 0) {
              asm volatile("st.shared.u32 [%0], %1;" ::"r"(epoch_s), "r"(epoch) : "memory");
              mbar_arrive(eready);
            }
          }
        }
#pragma unroll 1
        for (int n = WOPF0; n < WOPF; n++) {
          const int j = n + 6 - (n < -1) + (n >= 2) + (n >= 5);
          const char* q = P.wop[p] + (size_t)((h0 + HS * (j & 1)) * 192 + tg * 48 + w * 16 + lane) * 1280 + chunk_of(index_at(j >> 1, r, both), off) * 128;
          asm volatile("cp.async.wait_group %0;" ::"n"(PF_WIN - 1) : "memory");
          while ((int)(clk32() - due) < 0) __nanosleep(32);
          due = clk32() + WOPACE;
          if (lane < 16)
            asm volatile("cp.async.cg.shared.global.L2::128B [%0], [%1], 16;" ::"r"(sink + rot), "l"(q) : "memory");
          asm volatile("cp.async.commit_group;" ::: "memory");
          rot = rot == (PF_DEPTH - 1) * 960 ? 0 : rot + 960;
        }
        asm volatile("cp.async.wait_all;" ::: "memory");
      }
    }
    __syncwarp();
    TDUMP();
  } else {
    if (tid == 0) {
      asm volatile("prefetch.tensormap [%0];" ::"l"(&P.x[p]) : "memory");
      asm volatile("prefetch.tensormap [%0];" ::"l"(&P.wq[p]) : "memory");
    }
    {
      const int c = tid & 7, rr = tid >> 3;
      const uint32_t d = sbase + rr * 128 + ((c ^ (rr & 7)) << 4);
      const char* gw = P.wqp[p] + (size_t)(rr & 15) * 12288 + (h0 * 3 + (rr >> 4)) * 128 + c * 16;
      const uint32_t dw = sbase + SLOT_BYTES + (rr >> 4) * 8192 + (rr & 15) * 128 + ((c ^ (rr & 7)) << 4);
      const char* gx = P.xp[p] + (size_t)(tg * 192 + rr) * 1280 + c * 16;
#pragma unroll
      for (int i = 0; i < 4; i++) {
        asm volatile("cp.async.cg.shared.global [%0], [%1], 16;" ::"r"(dw + i * 2048), "l"(gw + i * 196608) : "memory");
        asm volatile("cp.async.cg.shared.global [%0], [%1], 16;" ::"r"(d + i * 6144), "l"(gx + i * 61440) : "memory");
      }
    }
    if (tid == 128) {
      mbar_init(full0, 1); mbar_init(full0 + 8, 1);
      for (int i = 0; i < NSLOT; i++) mbar_init(empty0 + 8 * i, 24);
      for (int i = 0; i < 3; i++) { mbar_init(xfull0 + 8 * i, 1); mbar_init(xempty0 + 8 * i, 4); }
      for (int i = 0; i < 9; i++) mbar_init(emptyo0 + 8 * i, 12);
      mbar_init(eready, 3);
      for (int i = 0; i < 5; i++) mbar_init(emptye0 + 8 * i, 12);
      for (int i = 0; i < 19; i++) mbar_init(fullo0 + 8 * i, 1 + ((0x3aau >> i) & 1));
      asm volatile("fence.mbarrier_init.release.cluster;" ::: "memory");
      for (int i = 0; i < 3; i++) mbar_expect_tx(xfull0 + 8 * i, XBUF_BYTES);
      mbar_arrive(full0); mbar_arrive(full0 + 8);
    }
    __syncwarp();
    asm volatile("barrier.cluster.arrive.relaxed.aligned;" ::: "memory");
    asm volatile("setmaxnreg.inc.sync.aligned.u32 160;");
    SNOW(sd_);
    asm volatile("barrier.cluster.wait.aligned;" ::: "memory");
    asm volatile("cp.async.wait_all;" ::: "memory");
    asm volatile("fence.proxy.async.shared::cta;" ::: "memory");
    asm volatile("bar.sync 4, 384;" ::: "memory");
    const int w = warp >> 2;
    const int hf = warp / 3 - w;
    uint32_t o0[48], o1[48];
    const uint32_t never = (out == nullptr);
    {
      Front f{{0, 0}, sbase, full0, mapa(empty0, lane & 1), never, w, lane, hf};
      f.run(o0, o1);
    }
#pragma unroll
    for (int i = 0; i < 12; i++) o0[i] ^= never;
    fence_regs(o0); fence_regs(o1);

    const int wt = tid & 127;
    uint32_t tok = w == 0 ? TOK0 : w == 1 ? TOK1 : TOK2;
    const bool finw = RSPLIT ? both || (r == 1) != (w == 2) : fin;
    if (RSPLIT && !fin) tok = w == 0 ? 0xfaaabu : w == 1 ? TOK1 : 0x2555au;
    const uint32_t xb = sbase + XBUF_OFF + w * XBUF_BYTES + wt * 16;
    mbar_wait(eready, 0);
    uint32_t tag;
    asm volatile("ld.shared.u32 %0, [%1];" : "=r"(tag) : "r"(epoch_s) : "memory");
    tag = __shfl_sync(0xffffffffu, ~tag & 1u, 0);
    float a[32];
    uint32_t x[16];
    const uint32_t toff = w * XBUF_BYTES + wt * 16;
    uint4* dst;
    auto publish = [&]() {
#pragma unroll
      for (int j = 0; j < 4; j++)
        asm volatile("st.relaxed.gpu.global.v4.b32 [%0], {%1, %2, %3, %4};"
                     ::"l"(dst + j * 128), "r"(x[4 * j]), "r"(x[4 * j + 1]), "r"(x[4 * j + 2]), "r"(x[4 * j + 3]) : "memory");
    };
    const uint32_t dbase = ((sbase & 0x3FFFFu) >> 4) | 0x10000u;
    uint64_t tbl = OSLOTS;
    uint32_t d0 = dbase + ((uint32_t)OSLOTS & 7u) * (SLOT_BYTES / 16), d1 = dbase + ((uint32_t)(OSLOTS >> 3) & 7u) * (SLOT_BYTES / 16);
    auto mkdst = [&](int k) {
      uint32_t u;
      asm volatile("ld.shared.u32 %0, [%1];" : "=r"(u) : "r"(dtab + 4 * k) : "memory");
      dst = reinterpret_cast<uint4*>(reinterpret_cast<char*>(g_part) + (u + toff));
      asm volatile("" : "+l"(dst));
    };
    auto prepare = [&](int t, bool early) {
      const int ci = index_at(t, r, both);
      const int k = early ? t >> 1 : (ci >> 1) + (RSPLIT && t == 9 && r);
      if (early || (ci & 1) != r || t == 9) {
        if (k == 0) mbar_wait(empty0 + 8 * 8, 1);
        else mbar_wait(xempty0 + 8 * w, (k - 1) & 1);
        if (early) {
          load_tile(x, sbase + ((d0 - dbase) << 4) + toff);
          mkdst(k);
        }
      } else {
        RSTAMP(0);
        mbar_wait(xfull0 + 8 * w, k & 1);
        RSTAMP(1);
        load_tile(x, xb);
        if (k < 4 || finw) {
          if (wt == 0) mbar_expect_tx(xfull0 + 8 * w, XBUF_BYTES);
          __syncwarp();
          if (lane == 0) mbar_arrive_cluster(mapa(xempty0 + 8 * w, r ^ 1) + ((x[0] | x[4] | x[8] | x[12]) & never));
        }
        if (k == 4) mkdst(4);
      }
      tbl >>= 6;
      tok >>= 2;
      d0 = dbase + ((uint32_t)tbl & 7u) * (SLOT_BYTES / 16);
      d1 = dbase + (((uint32_t)tbl >> 3) & 7u) * (SLOT_BYTES / 16);
      fence_regs(x);
    };
    auto epilogue = [&](int t, bool early) {
      const int ci = index_at(t, r, both);
      uint32_t z[16];
#pragma unroll
      for (int j = 0; j < 16; j++) z[j] = pack_bf16(a[2 * j], a[2 * j + 1]);
      if (early || (ci & 1) != r || t == 9) {
        const uint32_t rxb = mapa(xb, r ^ 1);
        const uint32_t rbar = mapa(xfull0 + 8 * w, r ^ 1);
        if (early) {
#pragma unroll
          for (int j = 0; j < 16; j++) z[j] = add_bf16x2(z[j], x[j]);
          fence_regs(z);
        }
        if (lane == 0 && t < 9) mbar_arrive(emptyo0 + 8 * t);
#pragma unroll
        for (int j = 0; j < 4; j++)
          asm volatile("st.async.weak.shared::cluster.mbarrier::complete_tx::bytes.v4.b32 [%0], {%1, %2, %3, %4}, [%5];"
                       ::"r"(rxb + j * 2048), "r"(z[4 * j]), "r"(z[4 * j + 1]), "r"(z[4 * j + 2]), "r"(z[4 * j + 3]), "r"(rbar) : "memory");
      } else {
        if (lane == 0) mbar_arrive(emptyo0 + 8 * t);
#pragma unroll
        for (int j = 0; j < 16; j++) x[j] = add_bf16x2(z[j], x[j]);
#pragma unroll
        for (int j = 0; j < 16; j += 4) x[j] = (x[j] & ~1u) | tag;
        fence_regs(x);
        publish();
      }
      ESTAMP(20 + t);
    };
    auto finalize = [&]() {
      const int c = chunk_of(both ? 8 + r : 9, off);
      TSTAMP(7);
      const uint4* tiles = g_part + (size_t)(grp * 10 + c) * 7 * (SLOT_BYTES / 16) + w * 512 + wt;
      auto load_g = [&](uint32_t (&y)[16], int q) {
#pragma unroll
        for (int j = 0; j < 4; j++)
          asm volatile("ld.relaxed.gpu.global.v4.b32 {%0, %1, %2, %3}, [%4];"
                       : "=r"(y[4 * j]), "=r"(y[4 * j + 1]), "=r"(y[4 * j + 2]), "=r"(y[4 * j + 3])
                       : "l"(tiles + q * (SLOT_BYTES / 16) + j * 128) : "memory");
      };
      const uint32_t tm = tag - 1u;
      const uint32_t t0 = clk32();
      auto settle = [&](uint32_t (&y)[16], int q) {
        while (true) {
          if (tile_ok(y, tm) || clk32() - t0 > SPIN_LIMIT) break;
          load_g(y, q);
        }
        add_tile(a, y);

      };
      mbar_wait(fullo0 + 8 * 14, 0);
      uint32_t ok = 1u;
#pragma unroll
      for (int h = 0; h < NPRE; h++) {
        if (h) {
          fence_regs(x);
          mbar_wait(fullo0 + 8 * (16 + w), 0);
        }
#pragma unroll
        for (int j = 0; j < 4; j++) {
          uint32_t y[2][4];
#pragma unroll
          for (int q = 0; q < 2; q++)
            asm volatile("ld.shared.v4.b32 {%0, %1, %2, %3}, [%4];"
                         : "=r"(y[q][0]), "=r"(y[q][1]), "=r"(y[q][2]), "=r"(y[q][3])
                         : "r"(oslot_addr(sbase, 12 + 2 * h + q) + toff + j * 2048) : "memory");
          ok &= lop3<0x42>(y[0][0], y[1][0], tm);
#pragma unroll
          for (int i = 0; i < 4; i++) {
            const uint32_t u = add_bf16x2(y[0][i], y[1][i]);
            if (!h) {
              x[4 * j + i] = u;
            } else {
              const uint32_t s = add_bf16x2(x[4 * j + i], u);
              a[8 * j + 2 * i] = __uint_as_float(s << 16);
              a[8 * j + 2 * i + 1] = __uint_as_float(s & 0xffff0000u);
            }
          }
        }
      }
      if (!ok) {
#pragma unroll
        for (int j = 0; j < 32; j++) a[j] = 0.f;
#pragma unroll 1
        for (int q = 0; q < 4; q++) {
          uint32_t x[16];
          load_g(x, q);
          settle(x, q);
        }
      }
      fence_regs(a);
      ZSTAMP(30);
      mbar_wait(fullo0 + 8 * 9, 0);
      asm volatile("bar.sync %0, 256;" ::"r"(1 + w) : "memory");
      wg_fence();
      {
        const uint64_t db = make_desc(oslot_addr(sbase, 18), 16, 1024);
#pragma unroll
        for (int j = 0; j < 12; j++) wgmma_n64_rs_tb(a, o0[4 * j], o0[4 * j + 1], o0[4 * j + 2], o0[4 * j + 3], db + 128 * j, 1);
        wg_commit();
      }
      {
        const uint64_t db = make_desc(oslot_addr(sbase, 19), 16, 1024);
#pragma unroll
        for (int j = 0; j < 12; j++) {
          wgmma_n64_rs_tb(a, o1[4 * j], o1[4 * j + 1], o1[4 * j + 2], o1[4 * j + 3], db + 128 * j, 1);
          if (j == TOKEN_AT && tok) asm volatile("bar.arrive %0, 256;" ::"r"(tok) : "memory");
        }
        wg_commit();
      }
      {
        uint32_t x[16], y0[16], y1[16], y2[16];
        wg_wait<1>();
        load_g(y0, 4); load_g(y1, 5); load_g(y2, 6);
        wg_wait<0>();
        fence_regs(a);
        TSTAMP(19);
        while (true) {
          const uint32_t k0 = tile_ok(y0, tm), k1 = tile_ok(y1, tm), k2 = tile_ok(y2, tm);
          if ((k0 & k1 & k2) || clk32() - t0 > SPIN_LIMIT) break;
          if (!k0) load_g(y0, 4);
          if (!k1) load_g(y1, 5);
          if (!k2) load_g(y2, 6);
        }
#pragma unroll
        for (int j = 0; j < 16; j++) y0[j] = add_bf16x2(add_bf16x2(y0[j], y1[j]), y2[j]);
        add_tile(a, y0);
        fence_regs(a);
        ZSTAMP(31);
        mbar_wait(xfull0 + 8 * w, !fin); load_tile(x, xb);
        add_tile(a, x);
      }
      TSTAMP(8);
      const int row = tg * 192 + w * 64 + (wt >> 5) * 16 + ((wt >> 2) & 7);
      uint4* d0 = reinterpret_cast<uint4*>(out + (size_t)row * 1280 + p * 640 + c * 64 + (wt & 3) * 8);
      const bool b0 = wt & 1, b1 = wt & 2;
      __syncwarp();
#pragma unroll
      for (int u = 0; u < 4; u++) {
        uint32_t x[4];
#pragma unroll
        for (int i = 0; i < 4; i++) {
          const int j = (u & 1) * 4 + i;
          x[i] = pack_bf16(a[4 * j + (u >> 1) * 2], a[4 * j + (u >> 1) * 2 + 1]);
        }
        uint32_t v;
        v = __shfl_xor_sync(0xffffffffu, b0 ? x[0] : x[1], 1); if (b0) x[0] = v; else x[1] = v;
        v = __shfl_xor_sync(0xffffffffu, b0 ? x[2] : x[3], 1); if (b0) x[2] = v; else x[3] = v;
        v = __shfl_xor_sync(0xffffffffu, b1 ? x[0] : x[2], 2); if (b1) x[0] = v; else x[2] = v;
        v = __shfl_xor_sync(0xffffffffu, b1 ? x[1] : x[3], 2); if (b1) x[1] = v; else x[3] = v;
        d0[(u & 1) * 4 + (u >> 1) * 8 * 160] = make_uint4(x[0], x[1], x[2], x[3]);
      }
      if (hp == 1 && tid == 0) asm volatile("red.relaxed.gpu.global.add.u32 [%0], 1;" ::"l"(P.epoch + grp) : "memory");
    };
#pragma unroll 1
    for (int t = 0; t < 10; t++) {
      if (t < 8 && !(t & 1)) {
        oproj_chunk<true>(a, o0, o1, t, d0, d1, fullo0, w, tok & 3u, [&]() { prepare(t, true); });
        TSTAMP(10 + t);
        epilogue(t, true);
        t++;
      }
      if (t == 9 && finw) { finalize(); break; }
      oproj_chunk<false>(a, o0, o1, t, d0, d1, fullo0, w, tok & 3u, [&]() { prepare(t, false); });
      TSTAMP(10 + t);
      epilogue(t, false);
    }
    TSTAMP(9);
    __syncwarp();
    TDUMP();
  }
}

typedef CUresult (*EncodeFn)(CUtensorMap*, CUtensorMapDataType, cuuint32_t, void*, const cuuint64_t*, const cuuint64_t*,
                             const cuuint32_t*, const cuuint32_t*, CUtensorMapInterleave, CUtensorMapSwizzle,
                             CUtensorMapL2promotion, CUtensorMapFloatOOBfill);

static void encode(EncodeFn fn, CUtensorMap* m, const void* ptr, int rank, const cuuint64_t* dims, const cuuint64_t* strides,
                   const cuuint32_t* box, int promo) {
  cuuint32_t es[5] = {1, 1, 1, 1, 1};
  fn(m, CU_TENSOR_MAP_DATA_TYPE_BFLOAT16, (cuuint32_t)rank, const_cast<void*>(ptr), dims, strides, box, es,
     CU_TENSOR_MAP_INTERLEAVE_NONE, CU_TENSOR_MAP_SWIZZLE_128B, (CUtensorMapL2promotion)promo,
     CU_TENSOR_MAP_FLOAT_OOB_FILL_NONE);
}
#define PR_X 3
#define PR_WQ 3
#define PR_K 3
#define PR_V 3
#define PR_WO 2

}

extern "C" void kernel_launch(void* const* d_in, const int* in_sizes, int n_in, void* d_out, int out_size) {
  using namespace fk;
  static Params params;
  static const void* cached[10] = {nullptr};
  static EncodeFn fn = nullptr;
  if (!fn) {
    void* f = nullptr;
    cudaDriverEntryPointQueryResult st;
    cudaGetDriverEntryPoint("cuTensorMapEncodeTiled", &f, cudaEnableDefault, &st);
    fn = (EncodeFn)f;
    void* e = nullptr;
    cudaGetSymbolAddress(&e, g_epoch);
    params.epoch = (unsigned int*)e;
    cudaFuncSetAttribute(fused_kernel, cudaFuncAttributeMaxDynamicSharedMemorySize, SMEM_BYTES);
  }
  bool same = true;
  for (int i = 0; i < 10; i++) same = same && (cached[i] == d_in[i]);
  if (!same) {
    for (int p = 0; p < 2; p++) {
      const void* x = d_in[5 * p + 0];
      const void* k = d_in[5 * p + 1];
      const void* v = d_in[5 * p + 2];
      const void* wq = d_in[5 * p + 3];
      const void* wo = d_in[5 * p + 4];
      params.kp[p] = (const char*)k; params.vp[p] = (const char*)v;
      params.wqp[p] = (const char*)wq; params.xp[p] = (const char*)x; params.wop[p] = (const char*)wo;
      {
        cuuint64_t d[2] = {640, 768}, s[1] = {1280};
        cuuint32_t b[2] = {64, 96};
        encode(fn, &params.x[p], x, 2, d, s, b, PR_X);
      }
      {
        cuuint64_t d[3] = {64, 640, 96}, s[2] = {12288, 128};
        cuuint32_t b[3] = {64, 64, 3};
        encode(fn, &params.wq[p], wq, 3, d, s, b, PR_WQ);
      }
      {
        cuuint64_t d[4] = {192, 48, 32, 16}, s[3] = {384, 18432, 589824};
        cuuint32_t b[4] = {64, 48, 1, 4};
        encode(fn, &params.k[p], k, 4, d, s, b, PR_K);
        encode(fn, &params.v[p], v, 4, d, s, b, PR_V);
      }
      {
        cuuint64_t d[2] = {640, 6144}, s[1] = {1280};
        cuuint32_t b[2] = {64, 192};
        encode(fn, &params.wo[p], wo, 2, d, s, b, PR_WO);
      }
    }
    for (int i = 0; i < 10; i++) cached[i] = d_in[i];
  }
  fused_kernel<<<128, NTHREADS, SMEM_BYTES>>>(params, (__nv_bfloat16*)d_out);
}
```

```cpp
#include <cuda_runtime.h>
#include <cuda_bf16.h>
#include <cuda.h>
#include <stdint.h>

#define PF_ON 1
#define PF_WIN 4
#define PF_WIN1 4
#define PF_WIN0 3
#define FDELAY 100
#define FS2 1
#define C1 0
#define FDELAY_C (1 + C1)
#define NPRE 2
#define PAR 1
#define YB 1
#define GATHB 0
#define DEFER 0
#define PRE3 1
#define YFIRST 1
#define PACE 485
#define SMI 1
#define PACE2 PACE
#define PH2 1
#define PF_TRIG 2
#define PF0_FROM 5
#define PF_NW 2
#define PF0 1
#define QMMA 4
#define TOKEN_AT 8
#define TOKEN_S 8
#define WOPF 6
#define WOPF0 -2
#define WOPACE 485
#define STAG 1
#define TOK0 0x3eaabu
#define TOK1 0x57ffdu
#define TOK2 0xa555au
#define FIRSTW 2
#define SPIN_LIMIT (1u << 27)

namespace fk {

#define HEADMAP 0
constexpr int HM = HEADMAP ? 1 : 2, HS = HEADMAP ? 16 : 1;
constexpr int SLOT_BYTES = 24576;
constexpr int NSLOT = 9;
constexpr int XBUF_BYTES = 8192;
constexpr int XBUF_OFF = 8 * SLOT_BYTES;
constexpr int BAR_OFF = NSLOT * SLOT_BYTES;
constexpr int FULLO = 192, FULLE = 272, EMPTYE = 360;
constexpr int SINK_OFF = BAR_OFF + 1024;
constexpr int PF_DEPTH = 9;
constexpr int SMEM_BYTES = SINK_OFF + PF_DEPTH * 960 + 1024;
constexpr int NTHREADS = 512;

#define PFIRSTP 1
#define TMLATE 2
#define TMT 416
#define ROT 0
#define TOPLD 2
#define PFE 1
#define PFT 0
#define PFT0 1
#define PFE_D 600
struct Params {
  CUtensorMap x[2], wq[2], k[2], v[2], wo[2];
  const char* kp[2]; const char* vp[2]; const char* wqp[2]; const char* xp[2]; const char* wop[2];
};
struct First { const char* wqp[2]; const char* xp[2]; };

constexpr int PART_BYTES = 8 * 10 * 7 * SLOT_BYTES;
__device__ uint4 g_part[PART_BYTES / 16 + 2];
#define PPAR 1
#define PART part
#define TSTAMP(i)
#define PSTAMP(i)
#define HSTAMP(i)
#define GSTAMP(a, b)
#define HSTAMP2(i)
#define CSTAMP(i)
#define TDUMP()

#define XSTAMP(i)
#define ESTAMP(i) TSTAMP(i)
#define QSTAMP(i)
#define RSTAMP(i)
#define OSTAMP(i)
#define ZSTAMP(i) TSTAMP(i)
#define FSTAMP(i)
#define SNOW(v)
#define SPUT(i, v)
__device__ __forceinline__ uint32_t smem_u32(const void* p) { return (uint32_t)__cvta_generic_to_shared(p); }
__device__ __forceinline__ void mbar_init(uint32_t bar, uint32_t cnt) {
  asm volatile("mbarrier.init.shared::cta.b64 [%0], %1;" ::"r"(bar), "r"(cnt) : "memory");
}
__device__ __forceinline__ void mbar_expect_tx(uint32_t bar, uint32_t bytes) {
  asm volatile("mbarrier.arrive.expect_tx.shared::cta.b64 _, [%0], %1;" ::"r"(bar), "r"(bytes) : "memory");
}
__device__ __forceinline__ uint32_t mapa(uint32_t addr, uint32_t cta) {
  uint32_t r;
  asm volatile("mapa.shared::cluster.u32 %0, %1, %2;" : "=r"(r) : "r"(addr), "r"(cta));
  return r;
}
__device__ __forceinline__ void mbar_arrive_cluster(uint32_t remote_bar) {
  asm volatile("mbarrier.arrive.shared::cluster.b64 _, [%0];" ::"r"(remote_bar) : "memory");
}
__device__ __forceinline__ uint32_t mbar_try(uint32_t bar, uint32_t parity) {
  uint32_t ok;
  asm volatile("{\n.reg .pred p;\nmbarrier.try_wait.parity.shared::cta.b64 p, [%1], %2;\nselp.u32 %0, 1, 0, p;\n}\n"
               : "=r"(ok) : "r"(bar), "r"(parity) : "memory");
  return ok;
}
__device__ __forceinline__ uint32_t mbar_test(uint32_t bar, uint32_t parity) {
  uint32_t ok;
  asm volatile("{\n.reg .pred p;\nmbarrier.test_wait.parity.shared::cta.b64 p, [%1], %2;\nselp.u32 %0, 1, 0, p;\n}\n"
               : "=r"(ok) : "r"(bar), "r"(parity) : "memory");
  return ok;
}
__device__ __forceinline__ uint32_t mbar_try_cluster(uint32_t bar, uint32_t parity) {
  uint32_t ok;
  asm volatile("{\n.reg .pred p;\nmbarrier.try_wait.parity.acquire.cluster.shared::cta.b64 p, [%1], %2;\nselp.u32 %0, 1, 0, p;\n}\n"
               : "=r"(ok) : "r"(bar), "r"(parity) : "memory");
  return ok;
}
__device__ __forceinline__ uint32_t clk32() {
  uint32_t t;
  asm volatile("mov.u32 %0, %%clock;" : "=r"(t));
  return t;
}
#define DBGREC(a, b)
__device__ __forceinline__ void mbar_wait(uint32_t bar, uint32_t parity) {
  if (mbar_try(bar, parity)) return;
  const uint32_t t0 = clk32();
  while (!mbar_try(bar, parity)) {
    if (clk32() - t0 > SPIN_LIMIT) { DBGREC(bar, parity); break; }
  }
}
__device__ __forceinline__ void mbar_wait_cluster(uint32_t bar, uint32_t parity) {
  if (mbar_try_cluster(bar, parity)) return;
  const uint32_t t0 = clk32();
  while (!mbar_try_cluster(bar, parity)) {
    if (clk32() - t0 > SPIN_LIMIT) break;
  }
}
__device__ __forceinline__ void cluster_sync() {
  asm volatile("barrier.cluster.arrive.release.aligned;\nbarrier.cluster.wait.acquire.aligned;\n" ::: "memory");
}
__device__ __forceinline__ void tma2d(uint32_t dst, const CUtensorMap* m, int c0, int c1, uint32_t bar) {
  asm volatile("cp.async.bulk.tensor.2d.shared::cluster.global.mbarrier::complete_tx::bytes [%0], [%1, {%3, %4}], [%2];"
               ::"r"(dst), "l"(m), "r"(bar), "r"(c0), "r"(c1) : "memory");
}
__device__ __forceinline__ void tma2d_mc(uint32_t dst, const CUtensorMap* m, int c0, int c1, uint32_t bar, uint16_t mask) {
  asm volatile("cp.async.bulk.tensor.2d.shared::cluster.global.mbarrier::complete_tx::bytes.multicast::cluster [%0], [%1, {%3, %4}], [%2], %5;"
               ::"r"(dst), "l"(m), "r"(bar), "r"(c0), "r"(c1), "h"(mask) : "memory");
}
__device__ __forceinline__ void tma3d(uint32_t dst, const CUtensorMap* m, int c0, int c1, int c2, uint32_t bar) {
  asm volatile("cp.async.bulk.tensor.3d.shared::cluster.global.mbarrier::complete_tx::bytes [%0], [%1, {%3, %4, %5}], [%2];"
               ::"r"(dst), "l"(m), "r"(bar), "r"(c0), "r"(c1), "r"(c2) : "memory");
}
__device__ __forceinline__ void tma4d(uint32_t dst, const CUtensorMap* m, int c0, int c1, int c2, int c3, uint32_t bar) {
  asm volatile("cp.async.bulk.tensor.4d.shared::cluster.global.mbarrier::complete_tx::bytes [%0], [%1, {%3, %4, %5, %6}], [%2];"
               ::"r"(dst), "l"(m), "r"(bar), "r"(c0), "r"(c1), "r"(c2), "r"(c3) : "memory");
}
__device__ __forceinline__ void bulk_g2s(uint32_t dst, const void* src, uint32_t bytes, uint32_t bar) {
  asm volatile("cp.async.bulk.shared::cluster.global.mbarrier::complete_tx::bytes [%0], [%1], %2, [%3];"
               ::"r"(dst), "l"(src), "r"(bytes), "r"(bar) : "memory");
}
__device__ __forceinline__ void mbar_arrive(uint32_t bar) {
  asm volatile("mbarrier.arrive.shared::cta.b64 _, [%0];" ::"r"(bar) : "memory");
}
__device__ __forceinline__ uint32_t touch_l2(const void* p) {
  uint32_t v;
  asm volatile("ld.global.cg.L2::128B.b32 %0, [%1];" : "=r"(v) : "l"(p));
  return v;
}
__device__ __forceinline__ unsigned ld_acquire(const unsigned* p) {
  unsigned v;
  asm volatile("ld.acquire.gpu.global.u32 %0, [%1];" : "=r"(v) : "l"(p) : "memory");
  return v;
}
__device__ __forceinline__ void wg_fence() { asm volatile("wgmma.fence.sync.aligned;" ::: "memory"); }
__device__ __forceinline__ void wg_commit() { asm volatile("wgmma.commit_group.sync.aligned;" ::: "memory"); }
template <int N> __device__ __forceinline__ void wg_wait() { asm volatile("wgmma.wait_group.sync.aligned %0;" ::"n"(N) : "memory"); }
template <int N> __device__ __forceinline__ void fence_regs(float (&d)[N]) {
#pragma unroll
  for (int i = 0; i < N; i++) asm volatile("" : "+f"(d[i])::"memory");
}
template <int N> __device__ __forceinline__ void fence_regs(uint32_t (&d)[N]) {
#pragma unroll
  for (int i = 0; i < N; i++) asm volatile("" : "+r"(d[i])::"memory");
}
template <int N> __device__ __forceinline__ void pin_regs(const uint32_t* d, uint32_t never, uint32_t addr) {
#pragma unroll
  for (int i = 0; i < N; i += 4)
    asm volatile("{\n.reg .pred p;\nsetp.ne.u32 p, %5, 0;\n@p st.shared.v4.b32 [%0], {%1, %2, %3, %4};\n}\n"
                 ::"r"(addr), "r"(d[i]), "r"(d[i + 1]), "r"(d[i + 2]), "r"(d[i + 3]), "r"(never) : "memory");
}
__device__ __forceinline__ uint32_t pack_bf16(float lo, float hi) {
  uint32_t r;
  asm("cvt.rn.bf16x2.f32 %0, %1, %2;" : "=r"(r) : "f"(hi), "f"(lo));
  return r;
}
__device__ __forceinline__ float ex2(float x) {
  float r;
  asm("ex2.approx.ftz.f32 %0, %1;" : "=f"(r) : "f"(x));
  return r;
}
__device__ __forceinline__ float rcp(float x) {
  float r;
  asm("rcp.approx.ftz.f32 %0, %1;" : "=f"(r) : "f"(x));
  return r;
}
__device__ __forceinline__ uint64_t make_desc(uint32_t addr, uint32_t lbo, uint32_t sbo) {
  return (uint64_t)((addr & 0x3FFFFu) >> 4) | ((uint64_t)(lbo >> 4) << 16) | ((uint64_t)(sbo >> 4) << 32) | (1ull << 62);
}

__device__ __forceinline__ void wgmma_n192_ss_tb(float (&d)[96], uint64_t da, uint64_t db, int scale_d) {
  asm volatile("{\n.reg .pred p;\nsetp.ne.b32 p, %98, 0;\n"
    "wgmma.mma_async.sync.aligned.m64n192k16.f32.bf16.bf16 "
    "{%0, %1, %2, %3, %4, %5, %6, %7, %8, %9, %10, %11, %12, %13, %14, %15, %16, %17, %18, %19, %20, %21, %22, %23, %24, %25, %26, %27, %28, %29, %30, %31, %32, %33, %34, %35, %36, %37, %38, %39, %40, %41, %42, %43, %44, %45, %46, %47, %48, %49, %50, %51, %52, %53, %54, %55, %56, %57, %58, %59, %60, %61, %62, %63, %64, %65, %66, %67, %68, %69, %70, %71, %72, %73, %74, %75, %76, %77, %78, %79, %80, %81, %82, %83, %84, %85, %86, %87, %88, %89, %90, %91, %92, %93, %94, %95}, "
    "%96, %97, p, 1, 1, 0, 1;\n}\n"
    : "+f"(d[0]), "+f"(d[1]), "+f"(d[2]), "+f"(d[3]), "+f"(d[4]), "+f"(d[5]), "+f"(d[6]), "+f"(d[7]), "+f"(d[8]), "+f"(d[9]), "+f"(d[10]), "+f"(d[11]), "+f"(d[12]), "+f"(d[13]), "+f"(d[14]), "+f"(d[15]), "+f"(d[16]), "+f"(d[17]), "+f"(d[18]), "+f"(d[19]), "+f"(d[20]), "+f"(d[21]), "+f"(d[22]), "+f"(d[23]), "+f"(d[24]), "+f"(d[25]), "+f"(d[26]), "+f"(d[27]), "+f"(d[28]), "+f"(d[29]), "+f"(d[30]), "+f"(d[31]), "+f"(d[32]), "+f"(d[33]), "+f"(d[34]), "+f"(d[35]), "+f"(d[36]), "+f"(d[37]), "+f"(d[38]), "+f"(d[39]), "+f"(d[40]), "+f"(d[41]), "+f"(d[42]), "+f"(d[43]), "+f"(d[44]), "+f"(d[45]), "+f"(d[46]), "+f"(d[47]), "+f"(d[48]), "+f"(d[49]), "+f"(d[50]), "+f"(d[51]), "+f"(d[52]), "+f"(d[53]), "+f"(d[54]), "+f"(d[55]), "+f"(d[56]), "+f"(d[57]), "+f"(d[58]), "+f"(d[59]), "+f"(d[60]), "+f"(d[61]), "+f"(d[62]), "+f"(d[63]), "+f"(d[64]), "+f"(d[65]), "+f"(d[66]), "+f"(d[67]), "+f"(d[68]), "+f"(d[69]), "+f"(d[70]), "+f"(d[71]), "+f"(d[72]), "+f"(d[73]), "+f"(d[74]), "+f"(d[75]), "+f"(d[76]), "+f"(d[77]), "+f"(d[78]), "+f"(d[79]), "+f"(d[80]), "+f"(d[81]), "+f"(d[82]), "+f"(d[83]), "+f"(d[84]), "+f"(d[85]), "+f"(d[86]), "+f"(d[87]), "+f"(d[88]), "+f"(d[89]), "+f"(d[90]), "+f"(d[91]), "+f"(d[92]), "+f"(d[93]), "+f"(d[94]), "+f"(d[95])
    : "l"(da), "l"(db), "r"(scale_d));
}
__device__ __forceinline__ void wgmma_n96_rs(float (&d)[48], uint32_t a0, uint32_t a1, uint32_t a2, uint32_t a3, uint64_t db, int scale_d) {
  asm volatile("{\n.reg .pred p;\nsetp.ne.b32 p, %53, 0;\n"
    "wgmma.mma_async.sync.aligned.m64n96k16.f32.bf16.bf16 "
    "{%0, %1, %2, %3, %4, %5, %6, %7, %8, %9, %10, %11, %12, %13, %14, %15, %16, %17, %18, %19, %20, %21, %22, %23, %24, %25, %26, %27, %28, %29, %30, %31, %32, %33, %34, %35, %36, %37, %38, %39, %40, %41, %42, %43, %44, %45, %46, %47}, "
    "{%48, %49, %50, %51}, %52, p, 1, 1, 0;\n}\n"
    : "+f"(d[0]), "+f"(d[1]), "+f"(d[2]), "+f"(d[3]), "+f"(d[4]), "+f"(d[5]), "+f"(d[6]), "+f"(d[7]), "+f"(d[8]), "+f"(d[9]), "+f"(d[10]), "+f"(d[11]), "+f"(d[12]), "+f"(d[13]), "+f"(d[14]), "+f"(d[15]), "+f"(d[16]), "+f"(d[17]), "+f"(d[18]), "+f"(d[19]), "+f"(d[20]), "+f"(d[21]), "+f"(d[22]), "+f"(d[23]), "+f"(d[24]), "+f"(d[25]), "+f"(d[26]), "+f"(d[27]), "+f"(d[28]), "+f"(d[29]), "+f"(d[30]), "+f"(d[31]), "+f"(d[32]), "+f"(d[33]), "+f"(d[34]), "+f"(d[35]), "+f"(d[36]), "+f"(d[37]), "+f"(d[38]), "+f"(d[39]), "+f"(d[40]), "+f"(d[41]), "+f"(d[42]), "+f"(d[43]), "+f"(d[44]), "+f"(d[45]), "+f"(d[46]), "+f"(d[47])
    : "r"(a0), "r"(a1), "r"(a2), "r"(a3), "l"(db), "r"(scale_d));
}
__device__ __forceinline__ void wgmma_n64_rs_tb(float (&d)[32], uint32_t a0, uint32_t a1, uint32_t a2, uint32_t a3, uint64_t db, int scale_d) {
  asm volatile("{\n.reg .pred p;\nsetp.ne.b32 p, %37, 0;\n"
    "wgmma.mma_async.sync.aligned.m64n64k16.f32.bf16.bf16 "
    "{%0, %1, %2, %3, %4, %5, %6, %7, %8, %9, %10, %11, %12, %13, %14, %15, %16, %17, %18, %19, %20, %21, %22, %23, %24, %25, %26, %27, %28, %29, %30, %31}, "
    "{%32, %33, %34, %35}, %36, p, 1, 1, 1;\n}\n"
    : "+f"(d[0]), "+f"(d[1]), "+f"(d[2]), "+f"(d[3]), "+f"(d[4]), "+f"(d[5]), "+f"(d[6]), "+f"(d[7]), "+f"(d[8]), "+f"(d[9]), "+f"(d[10]), "+f"(d[11]), "+f"(d[12]), "+f"(d[13]), "+f"(d[14]), "+f"(d[15]), "+f"(d[16]), "+f"(d[17]), "+f"(d[18]), "+f"(d[19]), "+f"(d[20]), "+f"(d[21]), "+f"(d[22]), "+f"(d[23]), "+f"(d[24]), "+f"(d[25]), "+f"(d[26]), "+f"(d[27]), "+f"(d[28]), "+f"(d[29]), "+f"(d[30]), "+f"(d[31])
    : "r"(a0), "r"(a1), "r"(a2), "r"(a3), "l"(db), "r"(scale_d));
}

__device__ __forceinline__ int chunk_of(int i, int off) { const int c = i + off; return c >= 10 ? c - 10 : c; }
__device__ __forceinline__ int pos_of(int i, int c) { return i - (i > chunk_of(c, 6)) - (i > chunk_of(c, 1)); }
#define SKEW 1
#define RSPLIT 0
__device__ __forceinline__ int index_at(int t, int r, bool both) {
  if (r == 0) return (t < 8 || both) ? (t ^ 1) : t;
  return (SKEW && !both && (t == 7 || t == 8)) ? 15 - t : t;
}

constexpr int KPOS = 43;
__device__ __forceinline__ void do_item(const Params& P, int i, int p, int tg, int h0, int r, uint32_t dst, uint32_t bar) {
  if (i >= 46) {
    const int h1 = i >= 49;
    tma4d(dst, &P.v[p], (i - 46 - 3 * h1) * 64, 0, h0 + HS * h1, tg * 4, bar);
  } else if (i >= KPOS && i < KPOS + 3) {
    tma4d(dst, &P.k[p], (i - KPOS) * 64, 0, h0 + HS, tg * 4, bar);
  } else if (i >= 20 && i < 23) {
    tma4d(dst, &P.k[p], (i - 20) * 64, 0, h0, tg * 4, bar);
  } else {
    const int hh = i >= 23;
    const int j = i - 23 * hh - 3 * (i >= KPOS);
    const int kc = j >> 1;
    if (!(j & 1)) tma2d_mc(dst + r * 12288, &P.x[p], kc * 64, tg * 192 + r * 96, bar, (uint16_t)3);
    else tma3d(dst, &P.wq[p], 0, kc * 64, (h0 + HS * hh) * 3, bar);
  }
}

struct Ring {
  uint32_t slot, phase;
  __device__ __forceinline__ void advance() {
    if (++slot == NSLOT) { slot = 0; phase ^= 1; }
  }
};

__device__ __forceinline__ void load_tile(uint32_t (&x)[16], uint32_t addr) {
#pragma unroll
  for (int j = 0; j < 4; j++)
    asm volatile("ld.shared.v4.b32 {%0, %1, %2, %3}, [%4];"
                 : "=r"(x[4 * j]), "=r"(x[4 * j + 1]), "=r"(x[4 * j + 2]), "=r"(x[4 * j + 3]) : "r"(addr + j * 2048) : "memory");
}
__device__ __forceinline__ void store_tile(uint32_t addr, const float (&a)[32]) {
#pragma unroll
  for (int j = 0; j < 4; j++)
    asm volatile("st.shared.v4.b32 [%0], {%1, %2, %3, %4};"
                 ::"r"(addr + j * 2048), "r"(pack_bf16(a[8 * j], a[8 * j + 1])), "r"(pack_bf16(a[8 * j + 2], a[8 * j + 3])),
                   "r"(pack_bf16(a[8 * j + 4], a[8 * j + 5])), "r"(pack_bf16(a[8 * j + 6], a[8 * j + 7])) : "memory");
}
__device__ __forceinline__ uint32_t add_bf16x2(uint32_t a, uint32_t b) {
  uint32_t r;
  asm("add.rn.bf16x2 %0, %1, %2;" : "=r"(r) : "r"(a), "r"(b));
  return r;
}
template <int LUT> __device__ __forceinline__ uint32_t lop3(uint32_t a, uint32_t b, uint32_t c) {
  uint32_t r;
  asm("lop3.b32 %0, %1, %2, %3, %4;" : "=r"(r) : "r"(a), "r"(b), "r"(c), "n"(LUT));
  return r;
}
__device__ __forceinline__ uint32_t tile_ok(const uint32_t (&y)[16], uint32_t tm) {
  return (y[0] ^ tm) & (y[4] ^ tm) & (y[8] ^ tm) & (y[12] ^ tm) & 1u;
}
__device__ __forceinline__ void add_tile(float (&a)[32], const uint32_t (&x)[16]) {
#pragma unroll
  for (int j = 0; j < 16; j++) {
    a[2 * j] += __uint_as_float(x[j] << 16);
    a[2 * j + 1] += __uint_as_float(x[j] & 0xffff0000u);
  }
}
constexpr uint64_t OSLOTS = 0x83d65683d6541d9ull;
__device__ __forceinline__ uint32_t oslot(uint32_t j) { return (uint32_t)(OSLOTS >> (3 * j)) & 7u; }

constexpr float SM_SCALE = 0.07216878364870322f * 1.4426950408889634f;
struct Front {
  Ring rg;
  uint32_t sbase, full0, rel0, never;
  int w, lane, hf;
  __device__ __forceinline__ uint32_t tsb() const { return full0 + 512 + w * 128; }
  __device__ __forceinline__ void release(uint32_t s) const { if (lane < 2) mbar_arrive_cluster(rel0 + 8 * s); }
  __device__ __forceinline__ uint32_t next() {
    const uint32_t s = rg.slot;
    mbar_wait(full0 + 8 * s, rg.phase);
    rg.advance();
    return s;
  }
  template <int N> __device__ __forceinline__ void landed() {
    asm volatile("cp.async.wait_group %0;" ::"n"(N) : "memory");
    asm volatile("fence.proxy.async.shared::cta;" ::: "memory");
    asm volatile("bar.sync 4, 384;" ::: "memory");
  }
  template <bool FIRST, int SPLIT = 0> __device__ __forceinline__ void qchunk(float (&acc)[96], uint32_t& sx, uint32_t& sw) {
    sx = next(); sw = next();
    const uint64_t da = make_desc(sbase + sx * SLOT_BYTES + w * 8192, 16, 1024);
    const uint64_t db = make_desc(sbase + sw * SLOT_BYTES, 8192, 1024);
    wg_fence();
#pragma unroll
    for (int s = 0; s < QMMA; s++) {
      if (SPLIT && s == SPLIT) landed<C1>();
      wgmma_n192_ss_tb(acc, da + 2 * s, db + 128 * s, !FIRST || s != 0);
    }
    wg_commit();
    if (SPLIT && C1) landed<0>();
  }
  __device__ __forceinline__ void qrest(float (&acc)[96], uint32_t (&qf)[48], uint32_t psx, uint32_t psw, int kc0, int tbase) {
#pragma unroll 1
    for (int kc = kc0; kc < 10; kc++) {
      uint32_t sx, sw;
      qchunk<false>(acc, sx, sw);
      QSTAMP(20 + kc);
      wg_wait<1>(); release(psx); release(psw);
      psx = sx; psw = sw;
    }
    wg_wait<0>();
    fence_regs(acc);
    release(psx); release(psw);
#pragma unroll
    for (int i = 24; i < 48; i++) qf[i] = pack_bf16(acc[2 * i], acc[2 * i + 1]);
    pin_regs<24>(qf + 24, never, full0);
#pragma unroll
    for (int i = 0; i < 24; i++) qf[i] = pack_bf16(acc[2 * i], acc[2 * i + 1]);
    pin_regs<24>(qf, never, full0);
    fence_regs(qf);
  }
  __device__ __forceinline__ void scores(float (&v)[24], const uint32_t (&qf)[48]) {
    float sacc[48];
    uint32_t ks[3];
#pragma unroll
    for (int dc = 0; dc < 3; dc++) {
      ks[dc] = next();
      const uint64_t db = make_desc(sbase + ks[dc] * SLOT_BYTES + w * 6144, 16, 1024);
      wg_fence();
#pragma unroll
      for (int s = 0; s < 4; s++) {
        const int j = dc * 4 + s;
        wgmma_n96_rs(sacc, qf[4 * j], qf[4 * j + 1], qf[4 * j + 2], qf[4 * j + 3], db + 2 * s, j != 0);
      }
    }
    wg_commit();
    wg_wait<0>();
    fence_regs(sacc);
    release(ks[0]); release(ks[1]); release(ks[2]);
#pragma unroll
    for (int i = 0; i < 24; i++) v[i] = hf ? sacc[24 + i] : sacc[i];
    fence_regs(v);
  }
  __device__ __forceinline__ void sm_max(const float (&v)[24], float& b0, float& b1) {
    float m0 = v[0], m1 = v[2];
#pragma unroll
    for (int t = 0; t < 6; t++) {
      m0 = fmaxf(m0, fmaxf(v[4 * t], v[4 * t + 1]));
      m1 = fmaxf(m1, fmaxf(v[4 * t + 2], v[4 * t + 3]));
    }
    m0 = fmaxf(m0, __shfl_xor_sync(0xffffffffu, m0, 1));
    m1 = fmaxf(m1, __shfl_xor_sync(0xffffffffu, m1, 1));
    m0 = fmaxf(m0, __shfl_xor_sync(0xffffffffu, m0, 2));
    m1 = fmaxf(m1, __shfl_xor_sync(0xffffffffu, m1, 2));
    b0 = m0 * SM_SCALE; b1 = m1 * SM_SCALE;
  }
  __device__ __forceinline__ void sm_exp(float (&v)[24], float& b0, float& b1) {
    float s0 = 0.f, s1 = 0.f;
#pragma unroll
    for (int t = 0; t < 6; t++) {
      v[4 * t] = ex2(fmaf(v[4 * t], SM_SCALE, -b0));
      v[4 * t + 1] = ex2(fmaf(v[4 * t + 1], SM_SCALE, -b0));
      v[4 * t + 2] = ex2(fmaf(v[4 * t + 2], SM_SCALE, -b1));
      v[4 * t + 3] = ex2(fmaf(v[4 * t + 3], SM_SCALE, -b1));
      s0 += v[4 * t] + v[4 * t + 1];
      s1 += v[4 * t + 2] + v[4 * t + 3];
    }
    s0 += __shfl_xor_sync(0xffffffffu, s0, 1);
    s1 += __shfl_xor_sync(0xffffffffu, s1, 1);
    s0 += __shfl_xor_sync(0xffffffffu, s0, 2);
    s1 += __shfl_xor_sync(0xffffffffu, s1, 2);
    b0 = rcp(s0); b1 = rcp(s1);
  }
  __device__ __forceinline__ void sm_pack(uint32_t (&pk)[12], const float (&v)[24], float r0, float r1) {
#pragma unroll
    for (int t = 0; t < 6; t++) {
      pk[2 * t] = pack_bf16(v[4 * t] * r0, v[4 * t + 1] * r0);
      pk[2 * t + 1] = pack_bf16(v[4 * t + 2] * r1, v[4 * t + 3] * r1);
    }
    pin_regs<12>(pk, never, full0);
    fence_regs(pk);
  }
  __device__ __forceinline__ void softmax(uint32_t (&pk)[12], float (&v)[24]) {
    float b0, b1;
    sm_max(v, b0, b1);
    sm_exp(v, b0, b1);
    sm_pack(pk, v, b0, b1);
  }
  __device__ __forceinline__ void expand(uint32_t (&pa)[24], uint32_t (&pk)[12]) {
    fence_regs(pk);
#pragma unroll
    for (int i = 0; i < 12; i++) {
      pa[i] = hf ? 0u : pk[i];
      pa[12 + i] = hf ? pk[i] : 0u;
    }
    fence_regs(pa);
  }
  __device__ __forceinline__ void pv(float (&oa)[32], const uint32_t (&pa)[24], int s, int parity) {
    mbar_wait(full0 + 8 * s, parity);
    const uint64_t db = make_desc(sbase + s * SLOT_BYTES + w * 6144, 16, 1024);
    wg_fence();
#pragma unroll
    for (int j = 0; j < 6; j++) wgmma_n64_rs_tb(oa, pa[4 * j], pa[4 * j + 1], pa[4 * j + 2], pa[4 * j + 3], db + 128 * j, j != 0);
  }
  __device__ __forceinline__ void pack16(uint32_t* o, const float (&oa)[32]) {
#pragma unroll
    for (int i = 0; i < 16; i++) o[i] = pack_bf16(oa[2 * i], oa[2 * i + 1]);
    pin_regs<16>(o, never, full0);
  }
  __device__ __forceinline__ void early(float (&a)[32], const uint32_t (&o0)[48], int t) {
    mbar_wait(full0 + FULLE + 8 * t, 0);
    const uint64_t db = make_desc(sbase + (4 + t) * SLOT_BYTES, 16, 1024);
    wg_fence();
#pragma unroll
    for (int j = 0; j < 12; j++)
      wgmma_n64_rs_tb(a, o0[4 * j], o0[4 * j + 1], o0[4 * j + 2], o0[4 * j + 3], db + 128 * j, j != 0);
    wg_commit();
  }
  __device__ __forceinline__ void park(float (&a)[32], int t) {
    fence_regs(a);
    if (lane == 0) mbar_arrive(full0 + EMPTYE + 8 * (t + 1));
    mbar_wait(full0 + EMPTYE + 8 * t, 0);
    uint32_t tid;
    asm volatile("mov.u32 %0, %%tid.x;" : "=r"(tid));
    store_tile(sbase + oslot(4 * t) * SLOT_BYTES + (tid >> 7) * XBUF_BYTES + (tid & 127) * 16, a);
  }
  __device__ __forceinline__ void run(uint32_t (&o0)[48], uint32_t (&o1)[48]) {
    uint32_t pk[12], pa[24];
    float v[24];
    {
      uint32_t qf[48];
      {
        float acc[96];
        uint32_t sx, sw;
        qchunk<true, FS2>(acc, sx, sw);
        { const int tbase = 1; (void)tbase; QSTAMP(20); }
        qrest(acc, qf, sx, sw, 1, 1);
      }
      TSTAMP(1);
      scores(v, qf);
      TSTAMP(2);
    }
    {
      uint32_t qf[48];
      {
        float acc[96];
        uint32_t ax, aw, bx, bw;
        qchunk<true>(acc, ax, aw);
        qchunk<false>(acc, bx, bw);
        softmax(pk, v);
        TSTAMP(3);
        wg_wait<1>(); release(ax); release(aw);
        qrest(acc, qf, bx, bw, 2, 4);
      }
      TSTAMP(4);
      scores(v, qf);
      TSTAMP(5);
    }
    {
      float oa[32], ob[32], oc[32];
      expand(pa, pk);
      float b0, b1;
      pv(oa, pa, 1, 1);
      sm_max(v, b0, b1);
      asm volatile("" : "+f"(b0), "+f"(b1));
      pv(ob, pa, 2, 1);
      sm_exp(v, b0, b1);
      fence_regs(v);
      asm volatile("" : "+f"(b0), "+f"(b1));
      pv(oc, pa, 3, 1);
      wg_commit();
      XSTAMP(20);
      sm_pack(pk, v, b0, b1);
      XSTAMP(21);
      wg_wait<0>();
      fence_regs(oa); fence_regs(ob); fence_regs(oc);
      XSTAMP(22);
      release(2); release(3);
      if (lane == 0) mbar_arrive(full0 + EMPTYE);
      pack16(o0, oa); pack16(o0 + 16, ob); pack16(o0 + 32, oc);
      fence_regs(o0);
    }
    {
      float oa[32], ob[32];
      early(oa, o0, 0);
      early(ob, o0, 1);
      XSTAMP(23);
      wg_wait<1>(); park(oa, 0);
      early(oa, o0, 2);
      wg_wait<1>(); park(ob, 1);
      early(ob, o0, 3);
      XSTAMP(24);
      wg_wait<1>(); park(oa, 2);
      wg_wait<0>(); park(ob, 3);
      XSTAMP(25);
      fence_regs(o0);
#pragma unroll
      for (int i = 0; i < 12; i++) o0[i] += never;
      fence_regs(o0);
      expand(pa, pk);
      pv(oa, pa, 8, 1);
      pv(ob, pa, 0, 0);
      wg_commit();
      XSTAMP(26);
      wg_wait<0>();
      fence_regs(oa); fence_regs(ob);
      XSTAMP(27);
      release(8); release(0);
      pack16(o1, oa); pack16(o1 + 16, ob);
      float oc[32];
      pv(oc, pa, 2, 0);
      wg_commit();
      XSTAMP(28);
      wg_wait<0>();
      fence_regs(oc);
      release(2);
      pack16(o1 + 32, oc);
    }
    TSTAMP(6);
  }
};

__device__ __forceinline__ uint32_t oslot_addr(uint32_t sbase, uint32_t j) { return sbase + oslot(j) * SLOT_BYTES; }
template <bool EARLY, class Mid>
__device__ __forceinline__ void oproj_chunk(float (&a)[32], const uint32_t (&o0)[48], const uint32_t (&o1)[48], int t,
                                            uint32_t d0, uint32_t d1, uint32_t fullo0, int w, uint32_t nxt, Mid mid) {
  auto tsb = [&]() { return fullo0 - FULLO + 512 + w * 128; };
  (void)tsb;
  OSTAMP(0);
  mbar_wait(fullo0 + 8 * t, 0);
  OSTAMP(1);
  if (!EARLY || t != 0 || w != FIRSTW) asm volatile("bar.sync %0, 256;" ::"r"(1 + w) : "memory");
  OSTAMP(2);
  wg_fence();
  if (!EARLY) {
    const uint64_t db = d0 | (0x40000040ull << 32);
#pragma unroll
    for (int j = 0; j < 12; j++)
      wgmma_n64_rs_tb(a, o0[4 * j], o0[4 * j + 1], o0[4 * j + 2], o0[4 * j + 3], db + 128 * j, j != 0);
  }
  {
    const uint64_t db = d1 | (0x40000040ull << 32);
#pragma unroll
    for (int j = 0; j < 12; j++) {
      wgmma_n64_rs_tb(a, o1[4 * j], o1[4 * j + 1], o1[4 * j + 2], o1[4 * j + 3], db + 128 * j, !EARLY || j != 0);
      if (j == (EARLY ? TOKEN_S : TOKEN_AT) && (EARLY || nxt)) asm volatile("bar.arrive %0, 256;" ::"r"(nxt) : "memory");
    }
    wg_commit();
  }
  OSTAMP(3);
  mid();
  OSTAMP(4);
  wg_wait<0>();
  fence_regs(a);
}

__global__ void __cluster_dims__(2, 1, 1) __launch_bounds__(NTHREADS, 1)
fused_kernel(const __grid_constant__ First F, __nv_bfloat16* __restrict__ out, char* part, const __grid_constant__ Params P) {
  extern __shared__ uint8_t smem_raw[];
  const uint32_t sbase = (smem_u32(smem_raw) + 1023u) & ~1023u;
  const uint32_t full0 = sbase + BAR_OFF;
  const uint32_t empty0 = full0 + 72;
  const uint32_t xfull0 = full0 + 144;
  const uint32_t xempty0 = full0 + 168;
  const uint32_t fullo0 = full0 + FULLO;
  const uint32_t emptyo0 = full0 + 400;
  const uint32_t eready = full0 + 344;
  const uint32_t epoch_s = full0 + 352;
  const uint32_t dtab = full0 + 480;
  const uint32_t emptye0 = full0 + EMPTYE;

  const int tid = threadIdx.x, lane = tid & 31;
  const int bid = blockIdx.x;
  const int hp = bid & 15, tg = (bid >> 4) & 3, p = bid >> 6;
  const int r = hp & 1;
  const int h0 = hp * HM;
  {
    const int c = tid & 7, rr = tid >> 3;
    const uint32_t d = sbase + rr * 128 + ((c ^ (rr & 7)) << 4);
    const char* gw = F.wqp[p] + (size_t)(rr & 15) * 12288 + (h0 * 3 + (rr >> 4)) * 128 + c * 16;
    const uint32_t dw = sbase + SLOT_BYTES + (rr >> 4) * 8192 + (rr & 15) * 128 + ((c ^ (rr & 7)) << 4);
    const char* gx = F.xp[p] + (size_t)(tg * 192 + rr) * 1280 + c * 16;
    uint32_t d_ = d, dw_ = dw;
    asm volatile("" : "+r"(d_), "+r"(dw_), "+l"(gw), "+l"(gx));
    if (tid < 384) {
#pragma unroll
      for (int i = 0; i < 4; i++) {
        if (i < FS2) asm volatile("cp.async.cg.shared.global [%0], [%1], 16;" ::"r"(dw_ + i * 2048), "l"(gw + i * 196608) : "memory");
        asm volatile("cp.async.cg.shared.global [%0], [%1], 16;" ::"r"(d_ + i * 6144), "l"(gx + i * 61440) : "memory");
      }
      asm volatile("cp.async.commit_group;" ::: "memory");
#pragma unroll
      for (int i = FS2; i < 4; i++)
        asm volatile("cp.async.cg.shared.global [%0], [%1], 16;" ::"r"(dw_ + i * 2048), "l"(gw + i * 196608) : "memory");
      asm volatile("cp.async.commit_group;" ::: "memory");
    }
    else if (tid == TMT) {
      asm volatile("prefetch.tensormap [%0];" ::"l"(&P.x[p]) : "memory");
      asm volatile("prefetch.tensormap [%0];" ::"l"(&P.wq[p]) : "memory");
    }
  }
  const int warp = __shfl_sync(0xffffffffu, tid >> 5, 0);
  auto tsb = [&]() { return full0 + 512 + (warp >> 2) * 128; };
  const int grp = p * 4 + tg;
  const int off = (hp >> 1) + (hp >> 3);
  const bool both = off == 0 || off == 5;
  const bool fin = r == 1 || both;

  if (warp >= 12) {
    asm volatile("setmaxnreg.dec.sync.aligned.u32 32;");
    if (tid == 384) {
#pragma unroll
      for (int i = 2; i < NSLOT; i++) mbar_init(full0 + 8 * i, 1);
      asm volatile("fence.mbarrier_init.release.cluster;" ::: "memory");
    }
    __syncwarp();
    asm volatile("barrier.cluster.arrive.relaxed.aligned;" ::: "memory");
    if (warp == 12) {
      SNOW(sa_);
      if (lane == 0) {
        if (C1) { mbar_arrive(full0 + 16); mbar_arrive(full0 + 24); }
#pragma unroll 1
        for (int c = 1 + C1; c < 5; c++) {
          if (c == FDELAY_C) { const uint32_t t0 = clk32(); while (clk32() - t0 < FDELAY) {} }
          mbar_expect_tx(full0 + 16 * c, SLOT_BYTES);
          tma2d(sbase + 2 * c * SLOT_BYTES, &P.x[p], c * 64, tg * 192, full0 + 16 * c);
          tma2d(sbase + 2 * c * SLOT_BYTES + 12288, &P.x[p], c * 64, tg * 192 + 96, full0 + 16 * c);
          if (c == 4) break;
          mbar_expect_tx(full0 + 8 + 16 * c, SLOT_BYTES);
          tma3d(sbase + (2 * c + 1) * SLOT_BYTES, &P.wq[p], 0, c * 64, h0 * 3, full0 + 8 + 16 * c);
        }
        asm volatile("prefetch.tensormap [%0];" ::"l"(&P.k[p]) : "memory");
        asm volatile("prefetch.tensormap [%0];" ::"l"(&P.v[p]) : "memory");
        asm volatile("prefetch.tensormap [%0];" ::"l"(&P.wo[p]) : "memory");
      }
      SNOW(sb_);
      __syncwarp();
      asm volatile("barrier.cluster.wait.aligned;" ::: "memory");
      if (lane == 0) {
        TSTAMP(3); CSTAMP(28);
        uint32_t slot = 0, phase = 1;
#pragma unroll 1
        for (int i = NSLOT; i < 49; i++) {
          mbar_wait(empty0 + 8 * slot, phase ^ 1);
          mbar_expect_tx(full0 + 8 * slot, SLOT_BYTES);
          do_item(P, i, p, tg, h0, r, sbase + slot * SLOT_BYTES, full0 + 8 * slot);
          if (++slot == NSLOT) { slot = 0; phase ^= 1; }
        }
        TSTAMP(2); CSTAMP(29);
#pragma unroll 1
        for (int e = 0; e < 23; e++) {
          int j;
          uint32_t bar;
          if (e < 11) {
            slot = (uint32_t)(0x20732087654ull >> (4 * e)) & 15u;
            if (e == 8) mbar_wait(emptye0 + 32, 0);
            else mbar_wait(empty0 + 8 * slot, e >= 5 && e < 8);
            if (e >= 4 && e < 7) {
              mbar_expect_tx(full0 + 8 * slot, SLOT_BYTES);
              do_item(P, 45 + e, p, tg, h0, r, sbase + slot * SLOT_BYTES, full0 + 8 * slot);
              continue;
            }
            j = e < 4 ? 4 * e : e - 6 + (e == 10);
          } else {
            const int n = e - 11;
            slot = oslot(n);
            mbar_wait(emptyo0 + 8 * (n >> 1), 0);
            asm volatile("fence.proxy.async.shared::cta;" ::: "memory");
            j = n + 6 + (n >= 2) + (n >= 5);
          }
          bar = e < 4 ? full0 + FULLE + 8 * e : fullo0 + 8 * (j >> 1);
          mbar_expect_tx(bar, SLOT_BYTES);
          tma2d(sbase + slot * SLOT_BYTES, &P.wo[p], chunk_of(index_at(j >> 1, r, both), off) * 64, (h0 + HS * (j & 1)) * 192, bar);
        }
        TSTAMP(1); CSTAMP(30);
        if (fin || RSPLIT) {
          const int lo = RSPLIT && !fin ? 2 * XBUF_BYTES : 0, hi = RSPLIT && !both && r ? 2 * XBUF_BYTES : 3 * XBUF_BYTES;
          const char* src = PART + (size_t)(grp * 10 + chunk_of(both ? 8 + r : 9, off)) * 7 * SLOT_BYTES;
          mbar_wait(emptyo0 + 8 * 6, 0);
          asm volatile("fence.proxy.async.shared::cta;" ::: "memory");
          mbar_expect_tx(fullo0 + 8 * 14, 2 * (hi - lo));
          TSTAMP(4);
          bulk_g2s(oslot_addr(sbase, 12) + lo, src + lo, hi - lo, fullo0 + 8 * 14);
          bulk_g2s(oslot_addr(sbase, 13) + lo, src + SLOT_BYTES + lo, hi - lo, fullo0 + 8 * 14);
          TSTAMP(5);
          mbar_wait(emptyo0 + 8 * 7, 0);
          asm volatile("fence.proxy.async.shared::cta;" ::: "memory");
          TSTAMP(6);
#pragma unroll 1
          for (int u = hi - XBUF_BYTES; u >= lo; u -= XBUF_BYTES) {
            const uint32_t bar = fullo0 + 8 * 16 + (u >> 10);
            mbar_expect_tx(bar, 2 * XBUF_BYTES);
            bulk_g2s(oslot_addr(sbase, 14) + u, src + 2 * SLOT_BYTES + u, XBUF_BYTES, bar);
            bulk_g2s(oslot_addr(sbase, 15) + u, src + 3 * SLOT_BYTES + u, XBUF_BYTES, bar);
          }
          TSTAMP(7);
        }
      }
    } else {
      const int w = warp - 13;
      unsigned epoch;
      asm volatile("ld.global.cg.u32 %0, [%1];" : "=r"(epoch) : "l"(part + PART_BYTES + 4 * grp));
      {
        uint32_t sink = sbase + SINK_OFF + (w * 20 + lane) * 16;
        int un = 0;
        uint32_t rot = 0;
        asm volatile("barrier.cluster.wait.aligned;" ::: "memory");
        if (PFE > 1) mbar_wait(full0 + 8 * PFE, 0);
        if (PFE_D) { const uint32_t t0 = clk32(); while (clk32() - t0 < PFE_D) __nanosleep(32); }
        if (lane < 16)
          asm volatile("cp.async.cg.shared.global.L2::128B [%0], [%1], 16;" ::"r"(sink + (PF_DEPTH - 1) * 960),
                       "l"(P.wqp[p] + (size_t)(lane * 4 + tg) * 12288 + h0 * 384 + w * 128 + 4 * 786432) : "memory");
        asm volatile("cp.async.commit_group;" ::: "memory");
        mbar_wait(full0 + 8 * PF_TRIG, 0);
        uint32_t due = clk32();
#pragma unroll 1
        for (int ph = PF0 ? -1 : 0; ph < 5; ph++) {
          const char* q;
          int nb = 4, nt = 3, nl = 16;
          uint32_t sb = 589824;
          if (ph == 1 || ph < 0) {
            q = P.wqp[p] + (size_t)(lane * 4 + tg) * 12288 + (h0 + HS * (ph > 0)) * 384 + w * 128;
            nb = 10; nt = 1; sb = 786432;
            if (ph < 0) {
              nl = 20;
              if (lane >= 16) { q = P.xp[p] + (size_t)(tg * 192 + hp * 12 + w * 4 + lane - 16) * 1280; sb = 128; }
              nb = 10 - PF0_FROM; q += PF0_FROM * sb;
            }
          } else {
            q = (ph < 3 ? P.kp[p] : P.vp[p]) + (size_t)(tg * 128 + h0 + HS * (ph == 2 || ph == 4)) * 18432 + (w * 16 + lane) * 128;
          }
#pragma unroll 1
          for (int b = 0; b < nb; b++, q += sb) {
            if (ph > 0 && mbar_test(emptye0 + 32, 0)) break;
#pragma unroll 1
            for (int t = 0; t < nt; t++) {
              if (ph < 0) asm volatile("cp.async.wait_group %0;" ::"n"(PF_WIN0 - 1) : "memory");
              else if (ph < PF_NW) asm volatile("cp.async.wait_group %0;" ::"n"(PF_WIN1 - 1) : "memory");
              else asm volatile("cp.async.wait_group %0;" ::"n"(PF_WIN - 1) : "memory");
              if (PACE) {
                while ((int)(clk32() - due) < 0) __nanosleep(32);
                due += ph >= PH2 ? PACE2 : PACE;
              }
              if (!(un & 1)) { PSTAMP(un >> 1); }
              if (lane < nl)
                asm volatile("cp.async.cg.shared.global.L2::128B [%0], [%1], 16;" ::"r"(sink + rot), "l"(q + t * 6144) : "memory");
              asm volatile("cp.async.commit_group;" ::: "memory");
              un++;
              rot = rot == (PF_DEPTH - 1) * 960 ? 0 : rot + 960;
            }
          }
          if (ph == 0) {
            if (lane < 5) {
              const int ci = 2 * lane + r, c = chunk_of(ci, off);
              asm volatile("st.shared.u32 [%0], %1;" ::"r"(dtab + 4 * lane), "r"(((grp * 10 + c) * 7 + pos_of(ci, c)) * SLOT_BYTES) : "memory");
            }
            __syncwarp();
            if (lane == 0) {
              asm volatile("st.shared.u32 [%0], %1;" ::"r"(epoch_s), "r"(epoch) : "memory");
              mbar_arrive(eready);
            }
          }
        }
#pragma unroll 1
        for (int n = WOPF0; n < WOPF; n++) {
          const int j = n + 6 - (n < -1) + (n >= 2) + (n >= 5);
          const char* q = P.wop[p] + (size_t)((h0 + HS * (j & 1)) * 192 + tg * 48 + w * 16 + lane) * 1280 + chunk_of(index_at(j >> 1, r, both), off) * 128;
          asm volatile("cp.async.wait_group %0;" ::"n"(PF_WIN - 1) : "memory");
          while ((int)(clk32() - due) < 0) __nanosleep(32);
          due = clk32() + WOPACE;
          if (lane < 16)
            asm volatile("cp.async.cg.shared.global.L2::128B [%0], [%1], 16;" ::"r"(sink + rot), "l"(q) : "memory");
          asm volatile("cp.async.commit_group;" ::: "memory");
          rot = rot == (PF_DEPTH - 1) * 960 ? 0 : rot + 960;
        }
        asm volatile("cp.async.wait_all;" ::: "memory");
      }
    }
    __syncwarp();
    TDUMP();
  } else {
    SNOW(se_);
    if (tid == 128) {
      mbar_init(full0, 1); mbar_init(full0 + 8, 1);
      for (int i = 0; i < NSLOT; i++) mbar_init(empty0 + 8 * i, 24);
      for (int i = 0; i < 3; i++) { mbar_init(xfull0 + 8 * i, 1); mbar_init(xempty0 + 8 * i, 4); }
      for (int i = 0; i < 9; i++) mbar_init(emptyo0 + 8 * i, 12);
      mbar_init(eready, 3);
      for (int i = 0; i < 5; i++) mbar_init(emptye0 + 8 * i, 12);
      for (int i = 0; i < 19; i++) mbar_init(fullo0 + 8 * i, 1 + ((0x3aau >> i) & 1));
      asm volatile("fence.mbarrier_init.release.cluster;" ::: "memory");
      for (int i = 0; i < 3; i++) mbar_expect_tx(xfull0 + 8 * i, XBUF_BYTES);
      mbar_arrive(full0); mbar_arrive(full0 + 8);
    }
    __syncwarp();
    asm volatile("barrier.cluster.arrive.relaxed.aligned;" ::: "memory");
    asm volatile("setmaxnreg.inc.sync.aligned.u32 160;");
    SNOW(sd_);
    asm volatile("barrier.cluster.wait.aligned;" ::: "memory");
    asm volatile("cp.async.wait_group %0;" ::"n"(1 + C1) : "memory");
    asm volatile("fence.proxy.async.shared::cta;" ::: "memory");
    asm volatile("bar.sync 4, 384;" ::: "memory");
    const int w = warp >> 2;
    const int hf = warp / 3 - w;
    uint32_t o0[48], o1[48];
    const uint32_t never = (out == nullptr);
    {
      Front f{{0, 0}, sbase, full0, mapa(empty0, lane & 1), never, w, lane, hf};
      f.run(o0, o1);
    }
#pragma unroll
    for (int i = 0; i < 12; i++) o0[i] ^= never;
    fence_regs(o0); fence_regs(o1);

    const int wt = tid & 127;
    uint32_t tok = w == 0 ? TOK0 : w == 1 ? TOK1 : TOK2;
    const bool finw = RSPLIT ? both || (r == 1) != (w == 2) : fin;
    if (RSPLIT && !fin) tok = w == 0 ? 0xfaaabu : w == 1 ? TOK1 : 0x2555au;
    const uint32_t xb = sbase + XBUF_OFF + w * XBUF_BYTES + wt * 16;
    mbar_wait(eready, 0);
    uint32_t tag;
    asm volatile("ld.shared.u32 %0, [%1];" : "=r"(tag) : "r"(epoch_s) : "memory");
    tag = __shfl_sync(0xffffffffu, ~tag & 1u, 0);
    float a[32];
    uint32_t x[16];
    const uint32_t toff = w * XBUF_BYTES + wt * 16;
    uint4* dst;
    auto publish = [&]() {
#pragma unroll
      for (int j = 0; j < 4; j++)
        asm volatile("st.relaxed.gpu.global.v4.b32 [%0], {%1, %2, %3, %4};"
                     ::"l"(dst + j * 128), "r"(x[4 * j]), "r"(x[4 * j + 1]), "r"(x[4 * j + 2]), "r"(x[4 * j + 3]) : "memory");
    };
    const uint32_t dbase = ((sbase & 0x3FFFFu) >> 4) | 0x10000u;
    uint64_t tbl = OSLOTS;
    uint32_t d0 = dbase + ((uint32_t)OSLOTS & 7u) * (SLOT_BYTES / 16), d1 = dbase + ((uint32_t)(OSLOTS >> 3) & 7u) * (SLOT_BYTES / 16);
    auto mkdst = [&](int k) {
      uint32_t u;
      asm volatile("ld.shared.u32 %0, [%1];" : "=r"(u) : "r"(dtab + 4 * k) : "memory");
      dst = reinterpret_cast<uint4*>(PART + (u + toff));
      asm volatile("" : "+l"(dst));
    };
    auto prepare = [&](int t, bool early) {
      const int ci = index_at(t, r, both);
      const int k = early ? t >> 1 : (ci >> 1) + (RSPLIT && t == 9 && r);
      if (early || (ci & 1) != r || t == 9) {
        if (k == 0) mbar_wait(empty0 + 8 * 8, 1);
        else mbar_wait(xempty0 + 8 * w, (k - 1) & 1);
        if (early) {
          load_tile(x, sbase + ((d0 - dbase) << 4) + toff);
          mkdst(k);
        }
      } else {
        RSTAMP(0);
        mbar_wait(xfull0 + 8 * w, k & 1);
        RSTAMP(1);
        load_tile(x, xb);
        if (k < 4 || finw) {
          if (wt == 0) mbar_expect_tx(xfull0 + 8 * w, XBUF_BYTES);
          __syncwarp();
          if (lane == 0) mbar_arrive_cluster(mapa(xempty0 + 8 * w, r ^ 1) + ((x[0] | x[4] | x[8] | x[12]) & never));
        }
        if (k == 4) mkdst(4);
      }
      tbl >>= 6;
      tok >>= 2;
      d0 = dbase + ((uint32_t)tbl & 7u) * (SLOT_BYTES / 16);
      d1 = dbase + (((uint32_t)tbl >> 3) & 7u) * (SLOT_BYTES / 16);
      fence_regs(x);
    };
    auto epilogue = [&](int t, bool early) {
      const int ci = index_at(t, r, both);
      uint32_t z[16];
#pragma unroll
      for (int j = 0; j < 16; j++) z[j] = pack_bf16(a[2 * j], a[2 * j + 1]);
      if (early || (ci & 1) != r || t == 9) {
        const uint32_t rxb = mapa(xb, r ^ 1);
        const uint32_t rbar = mapa(xfull0 + 8 * w, r ^ 1);
        if (early) {
#pragma unroll
          for (int j = 0; j < 16; j++) z[j] = add_bf16x2(z[j], x[j]);
          fence_regs(z);
        }
        if (lane == 0 && t < 9) mbar_arrive(emptyo0 + 8 * t);
#pragma unroll
        for (int j = 0; j < 4; j++)
          asm volatile("st.async.weak.shared::cluster.mbarrier::complete_tx::bytes.v4.b32 [%0], {%1, %2, %3, %4}, [%5];"
                       ::"r"(rxb + j * 2048), "r"(z[4 * j]), "r"(z[4 * j + 1]), "r"(z[4 * j + 2]), "r"(z[4 * j + 3]), "r"(rbar) : "memory");
      } else {
        if (lane == 0) mbar_arrive(emptyo0 + 8 * t);
#pragma unroll
        for (int j = 0; j < 16; j++) x[j] = add_bf16x2(z[j], x[j]);
#pragma unroll
        for (int j = 0; j < 16; j += 4) x[j] = (x[j] & ~1u) | tag;
        fence_regs(x);
        publish();
      }
      ESTAMP(20 + t);
    };
    auto finalize = [&]() {
      const int c = chunk_of(both ? 8 + r : 9, off);
      TSTAMP(7);
      const uint4* tiles = reinterpret_cast<const uint4*>(PART) + (size_t)(grp * 10 + c) * 7 * (SLOT_BYTES / 16) + w * 512 + wt;
      auto load_g = [&](uint32_t (&y)[16], int q) {
#pragma unroll
        for (int j = 0; j < 4; j++)
          asm volatile("ld.relaxed.gpu.global.v4.b32 {%0, %1, %2, %3}, [%4];"
                       : "=r"(y[4 * j]), "=r"(y[4 * j + 1]), "=r"(y[4 * j + 2]), "=r"(y[4 * j + 3])
                       : "l"(tiles + q * (SLOT_BYTES / 16) + j * 128) : "memory");
      };
      const uint32_t tm = tag - 1u;
      const uint32_t t0 = clk32();
      auto settle = [&](uint32_t (&y)[16], int q) {
        while (true) {
          if (tile_ok(y, tm) || clk32() - t0 > SPIN_LIMIT) break;
          load_g(y, q);
        }
        add_tile(a, y);

      };
      mbar_wait(fullo0 + 8 * 14, 0);
      uint32_t ok = 1u;
#pragma unroll
      for (int h = 0; h < NPRE; h++) {
        if (h) {
          fence_regs(x);
          mbar_wait(fullo0 + 8 * (16 + w), 0);
        }
#pragma unroll
        for (int j = 0; j < 4; j++) {
          uint32_t y[2][4];
#pragma unroll
          for (int q = 0; q < 2; q++)
            asm volatile("ld.shared.v4.b32 {%0, %1, %2, %3}, [%4];"
                         : "=r"(y[q][0]), "=r"(y[q][1]), "=r"(y[q][2]), "=r"(y[q][3])
                         : "r"(oslot_addr(sbase, 12 + 2 * h + q) + toff + j * 2048) : "memory");
          ok &= lop3<0x42>(y[0][0], y[1][0], tm);
#pragma unroll
          for (int i = 0; i < 4; i++) {
            const uint32_t u = add_bf16x2(y[0][i], y[1][i]);
            if (!h) {
              x[4 * j + i] = u;
            } else {
              const uint32_t s = add_bf16x2(x[4 * j + i], u);
              a[8 * j + 2 * i] = __uint_as_float(s << 16);
              a[8 * j + 2 * i + 1] = __uint_as_float(s & 0xffff0000u);
            }
          }
        }
      }
      if (!ok) {
#pragma unroll
        for (int j = 0; j < 32; j++) a[j] = 0.f;
#pragma unroll 1
        for (int q = 0; q < 4; q++) {
          uint32_t x[16];
          load_g(x, q);
          settle(x, q);
        }
      }
      fence_regs(a);
      ZSTAMP(30);
      mbar_wait(fullo0 + 8 * 9, 0);
      asm volatile("bar.sync %0, 256;" ::"r"(1 + w) : "memory");
      wg_fence();
      {
        const uint64_t db = make_desc(oslot_addr(sbase, 18), 16, 1024);
#pragma unroll
        for (int j = 0; j < 12; j++) wgmma_n64_rs_tb(a, o0[4 * j], o0[4 * j + 1], o0[4 * j + 2], o0[4 * j + 3], db + 128 * j, 1);
        wg_commit();
      }
      {
        const uint64_t db = make_desc(oslot_addr(sbase, 19), 16, 1024);
#pragma unroll
        for (int j = 0; j < 12; j++) {
          wgmma_n64_rs_tb(a, o1[4 * j], o1[4 * j + 1], o1[4 * j + 2], o1[4 * j + 3], db + 128 * j, 1);
          if (j == TOKEN_AT && tok) asm volatile("bar.arrive %0, 256;" ::"r"(tok) : "memory");
        }
        wg_commit();
      }
      {
        uint32_t x[16], y0[16], y1[16], y2[16];
        wg_wait<1>();
        load_g(y0, 4); load_g(y1, 5); load_g(y2, 6);
        wg_wait<0>();
        fence_regs(a);
        TSTAMP(19);
        while (true) {
          const uint32_t k0 = tile_ok(y0, tm), k1 = tile_ok(y1, tm), k2 = tile_ok(y2, tm);
          if ((k0 & k1 & k2) || clk32() - t0 > SPIN_LIMIT) break;
          if (!k0) load_g(y0, 4);
          if (!k1) load_g(y1, 5);
          if (!k2) load_g(y2, 6);
        }
#pragma unroll
        for (int j = 0; j < 16; j++) y0[j] = add_bf16x2(add_bf16x2(y0[j], y1[j]), y2[j]);
        add_tile(a, y0);
        fence_regs(a);
        ZSTAMP(31);
        mbar_wait(xfull0 + 8 * w, !fin); load_tile(x, xb);
        add_tile(a, x);
      }
      TSTAMP(8);
      const int row = tg * 192 + w * 64 + (wt >> 5) * 16 + ((wt >> 2) & 7);
      uint4* d0 = reinterpret_cast<uint4*>(out + (size_t)row * 1280 + p * 640 + c * 64 + (wt & 3) * 8);
      const bool b0 = wt & 1, b1 = wt & 2;
      __syncwarp();
#pragma unroll
      for (int u = 0; u < 4; u++) {
        uint32_t x[4];
#pragma unroll
        for (int i = 0; i < 4; i++) {
          const int j = (u & 1) * 4 + i;
          x[i] = pack_bf16(a[4 * j + (u >> 1) * 2], a[4 * j + (u >> 1) * 2 + 1]);
        }
        uint32_t v;
        v = __shfl_xor_sync(0xffffffffu, b0 ? x[0] : x[1], 1); if (b0) x[0] = v; else x[1] = v;
        v = __shfl_xor_sync(0xffffffffu, b0 ? x[2] : x[3], 1); if (b0) x[2] = v; else x[3] = v;
        v = __shfl_xor_sync(0xffffffffu, b1 ? x[0] : x[2], 2); if (b1) x[0] = v; else x[2] = v;
        v = __shfl_xor_sync(0xffffffffu, b1 ? x[1] : x[3], 2); if (b1) x[1] = v; else x[3] = v;
        d0[(u & 1) * 4 + (u >> 1) * 8 * 160] = make_uint4(x[0], x[1], x[2], x[3]);
      }
      if (hp == 1 && tid == 0) asm volatile("red.relaxed.gpu.global.add.u32 [%0], 1;" ::"l"(part + PART_BYTES + 4 * grp) : "memory");
    };
#pragma unroll 1
    for (int t = 0; t < 10; t++) {
      if (t < 8 && !(t & 1)) {
        oproj_chunk<true>(a, o0, o1, t, d0, d1, fullo0, w, tok & 3u, [&]() { prepare(t, true); });
        TSTAMP(10 + t);
        epilogue(t, true);
        t++;
      }
      if (t == 9 && finw) { finalize(); break; }
      oproj_chunk<false>(a, o0, o1, t, d0, d1, fullo0, w, tok & 3u, [&]() { prepare(t, false); });
      TSTAMP(10 + t);
      epilogue(t, false);
    }
    TSTAMP(9);
    __syncwarp();
    TDUMP();
  }
}

typedef CUresult (*EncodeFn)(CUtensorMap*, CUtensorMapDataType, cuuint32_t, void*, const cuuint64_t*, const cuuint64_t*,
                             const cuuint32_t*, const cuuint32_t*, CUtensorMapInterleave, CUtensorMapSwizzle,
                             CUtensorMapL2promotion, CUtensorMapFloatOOBfill);

static void encode(EncodeFn fn, CUtensorMap* m, const void* ptr, int rank, const cuuint64_t* dims, const cuuint64_t* strides,
                   const cuuint32_t* box, int promo) {
  cuuint32_t es[5] = {1, 1, 1, 1, 1};
  fn(m, CU_TENSOR_MAP_DATA_TYPE_BFLOAT16, (cuuint32_t)rank, const_cast<void*>(ptr), dims, strides, box, es,
     CU_TENSOR_MAP_INTERLEAVE_NONE, CU_TENSOR_MAP_SWIZZLE_128B, (CUtensorMapL2promotion)promo,
     CU_TENSOR_MAP_FLOAT_OOB_FILL_NONE);
}
#define PR_X 3
#define PR_WQ 2
#define PR_K 3
#define PR_V 3
#define PR_WO 2

}

extern "C" void kernel_launch(void* const* d_in, const int* in_sizes, int n_in, void* d_out, int out_size) {
  using namespace fk;
  static Params params;
  static const void* cached[10] = {nullptr};
  static EncodeFn fn = nullptr;
  static char* part = nullptr;
  if (!fn) {
    void* f = nullptr;
    cudaDriverEntryPointQueryResult st;
    cudaGetDriverEntryPoint("cuTensorMapEncodeTiled", &f, cudaEnableDefault, &st);
    fn = (EncodeFn)f;
    void* e = nullptr;
    cudaGetSymbolAddress(&e, g_part);
    part = (char*)e;
    cudaFuncSetAttribute(fused_kernel, cudaFuncAttributeMaxDynamicSharedMemorySize, SMEM_BYTES);
  }
  bool same = true;
  for (int i = 0; i < 10; i++) same = same && (cached[i] == d_in[i]);
  if (!same) {
    for (int p = 0; p < 2; p++) {
      const void* x = d_in[5 * p + 0];
      const void* k = d_in[5 * p + 1];
      const void* v = d_in[5 * p + 2];
      const void* wq = d_in[5 * p + 3];
      const void* wo = d_in[5 * p + 4];
      params.kp[p] = (const char*)k; params.vp[p] = (const char*)v;
      params.wqp[p] = (const char*)wq; params.xp[p] = (const char*)x; params.wop[p] = (const char*)wo;
      {
        cuuint64_t d[2] = {640, 768}, s[1] = {1280};
        cuuint32_t b[2] = {64, 96};
        encode(fn, &params.x[p], x, 2, d, s, b, PR_X);
      }
      {
        cuuint64_t d[3] = {64, 640, 96}, s[2] = {12288, 128};
        cuuint32_t b[3] = {64, 64, 3};
        encode(fn, &params.wq[p], wq, 3, d, s, b, PR_WQ);
      }
      {
        cuuint64_t d[4] = {192, 48, 32, 16}, s[3] = {384, 18432, 589824};
        cuuint32_t b[4] = {64, 48, 1, 4};
        encode(fn, &params.k[p], k, 4, d, s, b, PR_K);
        encode(fn, &params.v[p], v, 4, d, s, b, PR_V);
      }
      {
        cuuint64_t d[2] = {640, 6144}, s[1] = {1280};
        cuuint32_t b[2] = {64, 192};
        encode(fn, &params.wo[p], wo, 2, d, s, b, PR_WO);
      }
    }
    for (int i = 0; i < 10; i++) cached[i] = d_in[i];
  }
  const First first = {{params.wqp[0], params.wqp[1]}, {params.xp[0], params.xp[1]}};
  fused_kernel<<<128, NTHREADS, SMEM_BYTES>>>(first, (__nv_bfloat16*)d_out, part, params);
}
```

```cpp
#include <cuda_runtime.h>
#include <cuda_bf16.h>
#include <cuda.h>
#include <stdint.h>

#define PF_ON 1
#define PF_WIN 4
#define PF_WIN1 4
#define PF_WIN0 3
#define FDELAY 100
#define FS2 1
#define C1 0
#define FDELAY_C (1 + C1)
#define NPRE 2
#define PAR 1
#define YB 1
#define GATHB 0
#define DEFER 0
#define PRE3 1
#define G5 0
#define Y0P 3
#define YFIRST 1
#define PACE 485
#define SMI 1
#define PACE2 PACE
#define PH2 1
#define PF_TRIG 2
#define PF0_FROM 5
#define PF_NW 2
#define PF0 1
#define QMMA 4
#define TOKEN_AT 8
#define TOKEN_S 8
#define WOPF 6
#define WOPF0 -2
#define WOPACE 485
#define STAG 1
#define TOK0 0x3eaabu
#define TOK1 0x57ffdu
#define TOK2 0xa555au
#define FIRSTW 2
#define SPIN_LIMIT (1u << 27)

namespace fk {

#define HEADMAP 0
constexpr int HM = HEADMAP ? 1 : 2, HS = HEADMAP ? 16 : 1;
constexpr int SLOT_BYTES = 24576;
constexpr int NSLOT = 9;
constexpr int XBUF_BYTES = 8192;
constexpr int XBUF_OFF = 8 * SLOT_BYTES;
constexpr int BAR_OFF = NSLOT * SLOT_BYTES;
constexpr int FULLO = 192, FULLE = 272, EMPTYE = 360;
constexpr int SINK_OFF = BAR_OFF + 1024;
constexpr int PF_DEPTH = 9;
constexpr int SMEM_BYTES = SINK_OFF + PF_DEPTH * 960 + 1024;
constexpr int NTHREADS = 512;

#define PFIRSTP 1
#define TMLATE 2
#define TMT 416
#define ROT 0
#define TOPLD 2
#define PFE 1
#define PFT 0
#define PFT0 1
#define PFE_D 600
struct Params {
  CUtensorMap x[2], wq[2], k[2], v[2], wo[2];
  const char* kp[2]; const char* vp[2]; const char* wqp[2]; const char* xp[2]; const char* wop[2];
};
struct First { const char* wqp[2]; const char* xp[2]; };

constexpr int PART_BYTES = 8 * 10 * 7 * SLOT_BYTES;
__device__ uint4 g_part[PART_BYTES / 16 + 2];
#define PPAR 1
#define PART part
#define TSTAMP(i)
#define PSTAMP(i)
#define HSTAMP(i)
#define GSTAMP(a, b)
#define HSTAMP2(i)
#define CSTAMP(i)
#define TDUMP()

#define XSTAMP(i)
#define ESTAMP(i) TSTAMP(i)
#define QSTAMP(i)
#define RSTAMP(i)
#define OSTAMP(i)
#define ZSTAMP(i) TSTAMP(i)
#define FSTAMP(i)
#define SNOW(v)
#define SPUT(i, v)
__device__ __forceinline__ uint32_t smem_u32(const void* p) { return (uint32_t)__cvta_generic_to_shared(p); }
__device__ __forceinline__ void mbar_init(uint32_t bar, uint32_t cnt) {
  asm volatile("mbarrier.init.shared::cta.b64 [%0], %1;" ::"r"(bar), "r"(cnt) : "memory");
}
__device__ __forceinline__ void mbar_expect_tx(uint32_t bar, uint32_t bytes) {
  asm volatile("mbarrier.arrive.expect_tx.shared::cta.b64 _, [%0], %1;" ::"r"(bar), "r"(bytes) : "memory");
}
__device__ __forceinline__ uint32_t mapa(uint32_t addr, uint32_t cta) {
  uint32_t r;
  asm volatile("mapa.shared::cluster.u32 %0, %1, %2;" : "=r"(r) : "r"(addr), "r"(cta));
  return r;
}
__device__ __forceinline__ void mbar_arrive_cluster(uint32_t remote_bar) {
  asm volatile("mbarrier.arrive.shared::cluster.b64 _, [%0];" ::"r"(remote_bar) : "memory");
}
__device__ __forceinline__ uint32_t mbar_try(uint32_t bar, uint32_t parity) {
  uint32_t ok;
  asm volatile("{\n.reg .pred p;\nmbarrier.try_wait.parity.shared::cta.b64 p, [%1], %2;\nselp.u32 %0, 1, 0, p;\n}\n"
               : "=r"(ok) : "r"(bar), "r"(parity) : "memory");
  return ok;
}
__device__ __forceinline__ uint32_t mbar_test(uint32_t bar, uint32_t parity) {
  uint32_t ok;
  asm volatile("{\n.reg .pred p;\nmbarrier.test_wait.parity.shared::cta.b64 p, [%1], %2;\nselp.u32 %0, 1, 0, p;\n}\n"
               : "=r"(ok) : "r"(bar), "r"(parity) : "memory");
  return ok;
}
__device__ __forceinline__ uint32_t mbar_try_cluster(uint32_t bar, uint32_t parity) {
  uint32_t ok;
  asm volatile("{\n.reg .pred p;\nmbarrier.try_wait.parity.acquire.cluster.shared::cta.b64 p, [%1], %2;\nselp.u32 %0, 1, 0, p;\n}\n"
               : "=r"(ok) : "r"(bar), "r"(parity) : "memory");
  return ok;
}
__device__ __forceinline__ uint32_t clk32() {
  uint32_t t;
  asm volatile("mov.u32 %0, %%clock;" : "=r"(t));
  return t;
}
#define DBGREC(a, b)
__device__ __forceinline__ void mbar_wait(uint32_t bar, uint32_t parity) {
  if (mbar_try(bar, parity)) return;
  const uint32_t t0 = clk32();
  while (!mbar_try(bar, parity)) {
    if (clk32() - t0 > SPIN_LIMIT) { DBGREC(bar, parity); break; }
  }
}
__device__ __forceinline__ void mbar_wait_cluster(uint32_t bar, uint32_t parity) {
  if (mbar_try_cluster(bar, parity)) return;
  const uint32_t t0 = clk32();
  while (!mbar_try_cluster(bar, parity)) {
    if (clk32() - t0 > SPIN_LIMIT) break;
  }
}
__device__ __forceinline__ void cluster_sync() {
  asm volatile("barrier.cluster.arrive.release.aligned;\nbarrier.cluster.wait.acquire.aligned;\n" ::: "memory");
}
__device__ __forceinline__ void tma2d(uint32_t dst, const CUtensorMap* m, int c0, int c1, uint32_t bar) {
  asm volatile("cp.async.bulk.tensor.2d.shared::cluster.global.mbarrier::complete_tx::bytes [%0], [%1, {%3, %4}], [%2];"
               ::"r"(dst), "l"(m), "r"(bar), "r"(c0), "r"(c1) : "memory");
}
__device__ __forceinline__ void tma2d_mc(uint32_t dst, const CUtensorMap* m, int c0, int c1, uint32_t bar, uint16_t mask) {
  asm volatile("cp.async.bulk.tensor.2d.shared::cluster.global.mbarrier::complete_tx::bytes.multicast::cluster [%0], [%1, {%3, %4}], [%2], %5;"
               ::"r"(dst), "l"(m), "r"(bar), "r"(c0), "r"(c1), "h"(mask) : "memory");
}
__device__ __forceinline__ void tma3d(uint32_t dst, const CUtensorMap* m, int c0, int c1, int c2, uint32_t bar) {
  asm volatile("cp.async.bulk.tensor.3d.shared::cluster.global.mbarrier::complete_tx::bytes [%0], [%1, {%3, %4, %5}], [%2];"
               ::"r"(dst), "l"(m), "r"(bar), "r"(c0), "r"(c1), "r"(c2) : "memory");
}
__device__ __forceinline__ void tma4d(uint32_t dst, const CUtensorMap* m, int c0, int c1, int c2, int c3, uint32_t bar) {
  asm volatile("cp.async.bulk.tensor.4d.shared::cluster.global.mbarrier::complete_tx::bytes [%0], [%1, {%3, %4, %5, %6}], [%2];"
               ::"r"(dst), "l"(m), "r"(bar), "r"(c0), "r"(c1), "r"(c2), "r"(c3) : "memory");
}
__device__ __forceinline__ void bulk_g2s(uint32_t dst, const void* src, uint32_t bytes, uint32_t bar) {
  asm volatile("cp.async.bulk.shared::cluster.global.mbarrier::complete_tx::bytes [%0], [%1], %2, [%3];"
               ::"r"(dst), "l"(src), "r"(bytes), "r"(bar) : "memory");
}
__device__ __forceinline__ void mbar_arrive(uint32_t bar) {
  asm volatile("mbarrier.arrive.shared::cta.b64 _, [%0];" ::"r"(bar) : "memory");
}
__device__ __forceinline__ uint32_t touch_l2(const void* p) {
  uint32_t v;
  asm volatile("ld.global.cg.L2::128B.b32 %0, [%1];" : "=r"(v) : "l"(p));
  return v;
}
__device__ __forceinline__ unsigned ld_acquire(const unsigned* p) {
  unsigned v;
  asm volatile("ld.acquire.gpu.global.u32 %0, [%1];" : "=r"(v) : "l"(p) : "memory");
  return v;
}
__device__ __forceinline__ void wg_fence() { asm volatile("wgmma.fence.sync.aligned;" ::: "memory"); }
__device__ __forceinline__ void wg_commit() { asm volatile("wgmma.commit_group.sync.aligned;" ::: "memory"); }
template <int N> __device__ __forceinline__ void wg_wait() { asm volatile("wgmma.wait_group.sync.aligned %0;" ::"n"(N) : "memory"); }
template <int N> __device__ __forceinline__ void fence_regs(float (&d)[N]) {
#pragma unroll
  for (int i = 0; i < N; i++) asm volatile("" : "+f"(d[i])::"memory");
}
template <int N> __device__ __forceinline__ void fence_regs(uint32_t (&d)[N]) {
#pragma unroll
  for (int i = 0; i < N; i++) asm volatile("" : "+r"(d[i])::"memory");
}
template <int N> __device__ __forceinline__ void pin_regs(const uint32_t* d, uint32_t never, uint32_t addr) {
#pragma unroll
  for (int i = 0; i < N; i += 4)
    asm volatile("{\n.reg .pred p;\nsetp.ne.u32 p, %5, 0;\n@p st.shared.v4.b32 [%0], {%1, %2, %3, %4};\n}\n"
                 ::"r"(addr), "r"(d[i]), "r"(d[i + 1]), "r"(d[i + 2]), "r"(d[i + 3]), "r"(never) : "memory");
}
__device__ __forceinline__ uint32_t pack_bf16(float lo, float hi) {
  uint32_t r;
  asm("cvt.rn.bf16x2.f32 %0, %1, %2;" : "=r"(r) : "f"(hi), "f"(lo));
  return r;
}
__device__ __forceinline__ float ex2(float x) {
  float r;
  asm("ex2.approx.ftz.f32 %0, %1;" : "=f"(r) : "f"(x));
  return r;
}
__device__ __forceinline__ float rcp(float x) {
  float r;
  asm("rcp.approx.ftz.f32 %0, %1;" : "=f"(r) : "f"(x));
  return r;
}
__device__ __forceinline__ uint64_t make_desc(uint32_t addr, uint32_t lbo, uint32_t sbo) {
  return (uint64_t)((addr & 0x3FFFFu) >> 4) | ((uint64_t)(lbo >> 4) << 16) | ((uint64_t)(sbo >> 4) << 32) | (1ull << 62);
}

__device__ __forceinline__ void wgmma_n192_ss_tb(float (&d)[96], uint64_t da, uint64_t db, int scale_d) {
  asm volatile("{\n.reg .pred p;\nsetp.ne.b32 p, %98, 0;\n"
    "wgmma.mma_async.sync.aligned.m64n192k16.f32.bf16.bf16 "
    "{%0, %1, %2, %3, %4, %5, %6, %7, %8, %9, %10, %11, %12, %13, %14, %15, %16, %17, %18, %19, %20, %21, %22, %23, %24, %25, %26, %27, %28, %29, %30, %31, %32, %33, %34, %35, %36, %37, %38, %39, %40, %41, %42, %43, %44, %45, %46, %47, %48, %49, %50, %51, %52, %53, %54, %55, %56, %57, %58, %59, %60, %61, %62, %63, %64, %65, %66, %67, %68, %69, %70, %71, %72, %73, %74, %75, %76, %77, %78, %79, %80, %81, %82, %83, %84, %85, %86, %87, %88, %89, %90, %91, %92, %93, %94, %95}, "
    "%96, %97, p, 1, 1, 0, 1;\n}\n"
    : "+f"(d[0]), "+f"(d[1]), "+f"(d[2]), "+f"(d[3]), "+f"(d[4]), "+f"(d[5]), "+f"(d[6]), "+f"(d[7]), "+f"(d[8]), "+f"(d[9]), "+f"(d[10]), "+f"(d[11]), "+f"(d[12]), "+f"(d[13]), "+f"(d[14]), "+f"(d[15]), "+f"(d[16]), "+f"(d[17]), "+f"(d[18]), "+f"(d[19]), "+f"(d[20]), "+f"(d[21]), "+f"(d[22]), "+f"(d[23]), "+f"(d[24]), "+f"(d[25]), "+f"(d[26]), "+f"(d[27]), "+f"(d[28]), "+f"(d[29]), "+f"(d[30]), "+f"(d[31]), "+f"(d[32]), "+f"(d[33]), "+f"(d[34]), "+f"(d[35]), "+f"(d[36]), "+f"(d[37]), "+f"(d[38]), "+f"(d[39]), "+f"(d[40]), "+f"(d[41]), "+f"(d[42]), "+f"(d[43]), "+f"(d[44]), "+f"(d[45]), "+f"(d[46]), "+f"(d[47]), "+f"(d[48]), "+f"(d[49]), "+f"(d[50]), "+f"(d[51]), "+f"(d[52]), "+f"(d[53]), "+f"(d[54]), "+f"(d[55]), "+f"(d[56]), "+f"(d[57]), "+f"(d[58]), "+f"(d[59]), "+f"(d[60]), "+f"(d[61]), "+f"(d[62]), "+f"(d[63]), "+f"(d[64]), "+f"(d[65]), "+f"(d[66]), "+f"(d[67]), "+f"(d[68]), "+f"(d[69]), "+f"(d[70]), "+f"(d[71]), "+f"(d[72]), "+f"(d[73]), "+f"(d[74]), "+f"(d[75]), "+f"(d[76]), "+f"(d[77]), "+f"(d[78]), "+f"(d[79]), "+f"(d[80]), "+f"(d[81]), "+f"(d[82]), "+f"(d[83]), "+f"(d[84]), "+f"(d[85]), "+f"(d[86]), "+f"(d[87]), "+f"(d[88]), "+f"(d[89]), "+f"(d[90]), "+f"(d[91]), "+f"(d[92]), "+f"(d[93]), "+f"(d[94]), "+f"(d[95])
    : "l"(da), "l"(db), "r"(scale_d));
}
__device__ __forceinline__ void wgmma_n96_rs(float (&d)[48], uint32_t a0, uint32_t a1, uint32_t a2, uint32_t a3, uint64_t db, int scale_d) {
  asm volatile("{\n.reg .pred p;\nsetp.ne.b32 p, %53, 0;\n"
    "wgmma.mma_async.sync.aligned.m64n96k16.f32.bf16.bf16 "
    "{%0, %1, %2, %3, %4, %5, %6, %7, %8, %9, %10, %11, %12, %13, %14, %15, %16, %17, %18, %19, %20, %21, %22, %23, %24, %25, %26, %27, %28, %29, %30, %31, %32, %33, %34, %35, %36, %37, %38, %39, %40, %41, %42, %43, %44, %45, %46, %47}, "
    "{%48, %49, %50, %51}, %52, p, 1, 1, 0;\n}\n"
    : "+f"(d[0]), "+f"(d[1]), "+f"(d[2]), "+f"(d[3]), "+f"(d[4]), "+f"(d[5]), "+f"(d[6]), "+f"(d[7]), "+f"(d[8]), "+f"(d[9]), "+f"(d[10]), "+f"(d[11]), "+f"(d[12]), "+f"(d[13]), "+f"(d[14]), "+f"(d[15]), "+f"(d[16]), "+f"(d[17]), "+f"(d[18]), "+f"(d[19]), "+f"(d[20]), "+f"(d[21]), "+f"(d[22]), "+f"(d[23]), "+f"(d[24]), "+f"(d[25]), "+f"(d[26]), "+f"(d[27]), "+f"(d[28]), "+f"(d[29]), "+f"(d[30]), "+f"(d[31]), "+f"(d[32]), "+f"(d[33]), "+f"(d[34]), "+f"(d[35]), "+f"(d[36]), "+f"(d[37]), "+f"(d[38]), "+f"(d[39]), "+f"(d[40]), "+f"(d[41]), "+f"(d[42]), "+f"(d[43]), "+f"(d[44]), "+f"(d[45]), "+f"(d[46]), "+f"(d[47])
    : "r"(a0), "r"(a1), "r"(a2), "r"(a3), "l"(db), "r"(scale_d));
}
__device__ __forceinline__ void wgmma_n64_rs_tb(float (&d)[32], uint32_t a0, uint32_t a1, uint32_t a2, uint32_t a3, uint64_t db, int scale_d) {
  asm volatile("{\n.reg .pred p;\nsetp.ne.b32 p, %37, 0;\n"
    "wgmma.mma_async.sync.aligned.m64n64k16.f32.bf16.bf16 "
    "{%0, %1, %2, %3, %4, %5, %6, %7, %8, %9, %10, %11, %12, %13, %14, %15, %16, %17, %18, %19, %20, %21, %22, %23, %24, %25, %26, %27, %28, %29, %30, %31}, "
    "{%32, %33, %34, %35}, %36, p, 1, 1, 1;\n}\n"
    : "+f"(d[0]), "+f"(d[1]), "+f"(d[2]), "+f"(d[3]), "+f"(d[4]), "+f"(d[5]), "+f"(d[6]), "+f"(d[7]), "+f"(d[8]), "+f"(d[9]), "+f"(d[10]), "+f"(d[11]), "+f"(d[12]), "+f"(d[13]), "+f"(d[14]), "+f"(d[15]), "+f"(d[16]), "+f"(d[17]), "+f"(d[18]), "+f"(d[19]), "+f"(d[20]), "+f"(d[21]), "+f"(d[22]), "+f"(d[23]), "+f"(d[24]), "+f"(d[25]), "+f"(d[26]), "+f"(d[27]), "+f"(d[28]), "+f"(d[29]), "+f"(d[30]), "+f"(d[31])
    : "r"(a0), "r"(a1), "r"(a2), "r"(a3), "l"(db), "r"(scale_d));
}

__device__ __forceinline__ int chunk_of(int i, int off) { const int c = i + off; return c >= 10 ? c - 10 : c; }
__device__ __forceinline__ int pos_of(int i, int c) { return i - (i > chunk_of(c, 6)) - (i > chunk_of(c, 1)); }
#define SKEW 1
#define RSPLIT 0
__device__ __forceinline__ int index_at(int t, int r, bool both) {
  if (r == 0) return (t < 8 || both) ? (t ^ 1) : t;
  return (SKEW && !both && (t == 7 || t == 8)) ? 15 - t : t;
}

constexpr int KPOS = 43;
__device__ __forceinline__ void do_item(const Params& P, int i, int p, int tg, int h0, int r, uint32_t dst, uint32_t bar) {
  if (i >= 46) {
    const int h1 = i >= 49;
    tma4d(dst, &P.v[p], (i - 46 - 3 * h1) * 64, 0, h0 + HS * h1, tg * 4, bar);
  } else if (i >= KPOS && i < KPOS + 3) {
    tma4d(dst, &P.k[p], (i - KPOS) * 64, 0, h0 + HS, tg * 4, bar);
  } else if (i >= 20 && i < 23) {
    tma4d(dst, &P.k[p], (i - 20) * 64, 0, h0, tg * 4, bar);
  } else {
    const int hh = i >= 23;
    const int j = i - 23 * hh - 3 * (i >= KPOS);
    const int kc = j >> 1;
    if (!(j & 1)) tma2d_mc(dst + r * 12288, &P.x[p], kc * 64, tg * 192 + r * 96, bar, (uint16_t)3);
    else tma3d(dst, &P.wq[p], 0, kc * 64, (h0 + HS * hh) * 3, bar);
  }
}

struct Ring {
  uint32_t slot, phase;
  __device__ __forceinline__ void advance() {
    if (++slot == NSLOT) { slot = 0; phase ^= 1; }
  }
};

__device__ __forceinline__ void load_tile(uint32_t (&x)[16], uint32_t addr) {
#pragma unroll
  for (int j = 0; j < 4; j++)
    asm volatile("ld.shared.v4.b32 {%0, %1, %2, %3}, [%4];"
                 : "=r"(x[4 * j]), "=r"(x[4 * j + 1]), "=r"(x[4 * j + 2]), "=r"(x[4 * j + 3]) : "r"(addr + j * 2048) : "memory");
}
__device__ __forceinline__ void store_tile(uint32_t addr, const float (&a)[32]) {
#pragma unroll
  for (int j = 0; j < 4; j++)
    asm volatile("st.shared.v4.b32 [%0], {%1, %2, %3, %4};"
                 ::"r"(addr + j * 2048), "r"(pack_bf16(a[8 * j], a[8 * j + 1])), "r"(pack_bf16(a[8 * j + 2], a[8 * j + 3])),
                   "r"(pack_bf16(a[8 * j + 4], a[8 * j + 5])), "r"(pack_bf16(a[8 * j + 6], a[8 * j + 7])) : "memory");
}
__device__ __forceinline__ uint32_t add_bf16x2(uint32_t a, uint32_t b) {
  uint32_t r;
  asm("add.rn.bf16x2 %0, %1, %2;" : "=r"(r) : "r"(a), "r"(b));
  return r;
}
template <int LUT> __device__ __forceinline__ uint32_t lop3(uint32_t a, uint32_t b, uint32_t c) {
  uint32_t r;
  asm("lop3.b32 %0, %1, %2, %3, %4;" : "=r"(r) : "r"(a), "r"(b), "r"(c), "n"(LUT));
  return r;
}
__device__ __forceinline__ uint32_t tile_ok(const uint32_t (&y)[16], uint32_t tm) {
  return (y[0] ^ tm) & (y[4] ^ tm) & (y[8] ^ tm) & (y[12] ^ tm) & 1u;
}
__device__ __forceinline__ void add_tile(float (&a)[32], const uint32_t (&x)[16]) {
#pragma unroll
  for (int j = 0; j < 16; j++) {
    a[2 * j] += __uint_as_float(x[j] << 16);
    a[2 * j + 1] += __uint_as_float(x[j] & 0xffff0000u);
  }
}
constexpr uint64_t OSLOTS = 0x83d65683d6541d9ull;
__device__ __forceinline__ uint32_t oslot(uint32_t j) { return (uint32_t)(OSLOTS >> (3 * j)) & 7u; }

constexpr float SM_SCALE = 0.07216878364870322f * 1.4426950408889634f;
struct Front {
  Ring rg;
  uint32_t sbase, full0, rel0, never;
  int w, lane, hf;
  __device__ __forceinline__ uint32_t tsb() const { return full0 + 512 + w * 128; }
  __device__ __forceinline__ void release(uint32_t s) const { if (lane < 2) mbar_arrive_cluster(rel0 + 8 * s); }
  __device__ __forceinline__ uint32_t next() {
    const uint32_t s = rg.slot;
    mbar_wait(full0 + 8 * s, rg.phase);
    rg.advance();
    return s;
  }
  template <int N> __device__ __forceinline__ void landed() {
    asm volatile("cp.async.wait_group %0;" ::"n"(N) : "memory");
    asm volatile("fence.proxy.async.shared::cta;" ::: "memory");
    asm volatile("bar.sync 4, 384;" ::: "memory");
  }
  template <bool FIRST, int SPLIT = 0> __device__ __forceinline__ void qchunk(float (&acc)[96], uint32_t& sx, uint32_t& sw) {
    sx = next(); sw = next();
    const uint64_t da = make_desc(sbase + sx * SLOT_BYTES + w * 8192, 16, 1024);
    const uint64_t db = make_desc(sbase + sw * SLOT_BYTES, 8192, 1024);
    wg_fence();
#pragma unroll
    for (int s = 0; s < QMMA; s++) {
      if (SPLIT && s == SPLIT) landed<C1>();
      wgmma_n192_ss_tb(acc, da + 2 * s, db + 128 * s, !FIRST || s != 0);
    }
    wg_commit();
    if (SPLIT && C1) landed<0>();
  }
  __device__ __forceinline__ void qrest(float (&acc)[96], uint32_t (&qf)[48], uint32_t psx, uint32_t psw, int kc0, int tbase) {
#pragma unroll 1
    for (int kc = kc0; kc < 10; kc++) {
      uint32_t sx, sw;
      qchunk<false>(acc, sx, sw);
      QSTAMP(20 + kc);
      wg_wait<1>(); release(psx); release(psw);
      psx = sx; psw = sw;
    }
    wg_wait<0>();
    fence_regs(acc);
    release(psx); release(psw);
#pragma unroll
    for (int i = 24; i < 48; i++) qf[i] = pack_bf16(acc[2 * i], acc[2 * i + 1]);
    pin_regs<24>(qf + 24, never, full0);
#pragma unroll
    for (int i = 0; i < 24; i++) qf[i] = pack_bf16(acc[2 * i], acc[2 * i + 1]);
    pin_regs<24>(qf, never, full0);
    fence_regs(qf);
  }
  __device__ __forceinline__ void scores(float (&v)[24], const uint32_t (&qf)[48]) {
    float sacc[48];
    uint32_t ks[3];
#pragma unroll
    for (int dc = 0; dc < 3; dc++) {
      ks[dc] = next();
      const uint64_t db = make_desc(sbase + ks[dc] * SLOT_BYTES + w * 6144, 16, 1024);
      wg_fence();
#pragma unroll
      for (int s = 0; s < 4; s++) {
        const int j = dc * 4 + s;
        wgmma_n96_rs(sacc, qf[4 * j], qf[4 * j + 1], qf[4 * j + 2], qf[4 * j + 3], db + 2 * s, j != 0);
      }
    }
    wg_commit();
    wg_wait<0>();
    fence_regs(sacc);
    release(ks[0]); release(ks[1]); release(ks[2]);
#pragma unroll
    for (int i = 0; i < 24; i++) v[i] = hf ? sacc[24 + i] : sacc[i];
    fence_regs(v);
  }
  __device__ __forceinline__ void sm_max(const float (&v)[24], float& b0, float& b1) {
    float m0 = v[0], m1 = v[2];
#pragma unroll
    for (int t = 0; t < 6; t++) {
      m0 = fmaxf(m0, fmaxf(v[4 * t], v[4 * t + 1]));
      m1 = fmaxf(m1, fmaxf(v[4 * t + 2], v[4 * t + 3]));
    }
    m0 = fmaxf(m0, __shfl_xor_sync(0xffffffffu, m0, 1));
    m1 = fmaxf(m1, __shfl_xor_sync(0xffffffffu, m1, 1));
    m0 = fmaxf(m0, __shfl_xor_sync(0xffffffffu, m0, 2));
    m1 = fmaxf(m1, __shfl_xor_sync(0xffffffffu, m1, 2));
    b0 = m0 * SM_SCALE; b1 = m1 * SM_SCALE;
  }
  __device__ __forceinline__ void sm_exp(float (&v)[24], float& b0, float& b1) {
    float s0 = 0.f, s1 = 0.f;
#pragma unroll
    for (int t = 0; t < 6; t++) {
      v[4 * t] = ex2(fmaf(v[4 * t], SM_SCALE, -b0));
      v[4 * t + 1] = ex2(fmaf(v[4 * t + 1], SM_SCALE, -b0));
      v[4 * t + 2] = ex2(fmaf(v[4 * t + 2], SM_SCALE, -b1));
      v[4 * t + 3] = ex2(fmaf(v[4 * t + 3], SM_SCALE, -b1));
      s0 += v[4 * t] + v[4 * t + 1];
      s1 += v[4 * t + 2] + v[4 * t + 3];
    }
    s0 += __shfl_xor_sync(0xffffffffu, s0, 1);
    s1 += __shfl_xor_sync(0xffffffffu, s1, 1);
    s0 += __shfl_xor_sync(0xffffffffu, s0, 2);
    s1 += __shfl_xor_sync(0xffffffffu, s1, 2);
    b0 = rcp(s0); b1 = rcp(s1);
  }
  __device__ __forceinline__ void sm_pack(uint32_t (&pk)[12], const float (&v)[24], float r0, float r1) {
#pragma unroll
    for (int t = 0; t < 6; t++) {
      pk[2 * t] = pack_bf16(v[4 * t] * r0, v[4 * t + 1] * r0);
      pk[2 * t + 1] = pack_bf16(v[4 * t + 2] * r1, v[4 * t + 3] * r1);
    }
    pin_regs<12>(pk, never, full0);
    fence_regs(pk);
  }
  __device__ __forceinline__ void softmax(uint32_t (&pk)[12], float (&v)[24]) {
    float b0, b1;
    sm_max(v, b0, b1);
    sm_exp(v, b0, b1);
    sm_pack(pk, v, b0, b1);
  }
  __device__ __forceinline__ void expand(uint32_t (&pa)[24], uint32_t (&pk)[12]) {
    fence_regs(pk);
#pragma unroll
    for (int i = 0; i < 12; i++) {
      pa[i] = hf ? 0u : pk[i];
      pa[12 + i] = hf ? pk[i] : 0u;
    }
    fence_regs(pa);
  }
  __device__ __forceinline__ void pv(float (&oa)[32], const uint32_t (&pa)[24], int s, int parity) {
    mbar_wait(full0 + 8 * s, parity);
    const uint64_t db = make_desc(sbase + s * SLOT_BYTES + w * 6144, 16, 1024);
    wg_fence();
#pragma unroll
    for (int j = 0; j < 6; j++) wgmma_n64_rs_tb(oa, pa[4 * j], pa[4 * j + 1], pa[4 * j + 2], pa[4 * j + 3], db + 128 * j, j != 0);
  }
  __device__ __forceinline__ void pack16(uint32_t* o, const float (&oa)[32]) {
#pragma unroll
    for (int i = 0; i < 16; i++) o[i] = pack_bf16(oa[2 * i], oa[2 * i + 1]);
    pin_regs<16>(o, never, full0);
  }
  __device__ __forceinline__ void early(float (&a)[32], const uint32_t (&o0)[48], int t) {
    mbar_wait(full0 + FULLE + 8 * t, 0);
    const uint64_t db = make_desc(sbase + (4 + t) * SLOT_BYTES, 16, 1024);
    wg_fence();
#pragma unroll
    for (int j = 0; j < 12; j++)
      wgmma_n64_rs_tb(a, o0[4 * j], o0[4 * j + 1], o0[4 * j + 2], o0[4 * j + 3], db + 128 * j, j != 0);
    wg_commit();
  }
  __device__ __forceinline__ void park(float (&a)[32], int t) {
    fence_regs(a);
    if (lane == 0) mbar_arrive(full0 + EMPTYE + 8 * (t + 1));
    mbar_wait(full0 + EMPTYE + 8 * t, 0);
    uint32_t tid;
    asm volatile("mov.u32 %0, %%tid.x;" : "=r"(tid));
    store_tile(sbase + oslot(4 * t) * SLOT_BYTES + (tid >> 7) * XBUF_BYTES + (tid & 127) * 16, a);
  }
  __device__ __forceinline__ void run(uint32_t (&o0)[48], uint32_t (&o1)[48]) {
    uint32_t pk[12], pa[24];
    float v[24];
    {
      uint32_t qf[48];
      {
        float acc[96];
        uint32_t sx, sw;
        qchunk<true, FS2>(acc, sx, sw);
        { const int tbase = 1; (void)tbase; QSTAMP(20); }
        qrest(acc, qf, sx, sw, 1, 1);
      }
      TSTAMP(1);
      scores(v, qf);
      TSTAMP(2);
    }
    {
      uint32_t qf[48];
      {
        float acc[96];
        uint32_t ax, aw, bx, bw;
        qchunk<true>(acc, ax, aw);
        qchunk<false>(acc, bx, bw);
        softmax(pk, v);
        TSTAMP(3);
        wg_wait<1>(); release(ax); release(aw);
        qrest(acc, qf, bx, bw, 2, 4);
      }
      TSTAMP(4);
      scores(v, qf);
      TSTAMP(5);
    }
    {
      float oa[32], ob[32], oc[32];
      expand(pa, pk);
      float b0, b1;
      pv(oa, pa, 1, 1);
      sm_max(v, b0, b1);
      asm volatile("" : "+f"(b0), "+f"(b1));
      pv(ob, pa, 2, 1);
      sm_exp(v, b0, b1);
      fence_regs(v);
      asm volatile("" : "+f"(b0), "+f"(b1));
      pv(oc, pa, 3, 1);
      wg_commit();
      XSTAMP(20);
      sm_pack(pk, v, b0, b1);
      XSTAMP(21);
      wg_wait<0>();
      fence_regs(oa); fence_regs(ob); fence_regs(oc);
      XSTAMP(22);
      release(2); release(3);
      if (lane == 0) mbar_arrive(full0 + EMPTYE);
      pack16(o0, oa); pack16(o0 + 16, ob); pack16(o0 + 32, oc);
      fence_regs(o0);
    }
    {
      float oa[32], ob[32];
      early(oa, o0, 0);
      early(ob, o0, 1);
      XSTAMP(23);
      wg_wait<1>(); park(oa, 0);
      early(oa, o0, 2);
      wg_wait<1>(); park(ob, 1);
      early(ob, o0, 3);
      XSTAMP(24);
      wg_wait<1>(); park(oa, 2);
      wg_wait<0>(); park(ob, 3);
      XSTAMP(25);
      fence_regs(o0);
#pragma unroll
      for (int i = 0; i < 12; i++) o0[i] += never;
      fence_regs(o0);
      expand(pa, pk);
      pv(oa, pa, 8, 1);
      pv(ob, pa, 0, 0);
      wg_commit();
      XSTAMP(26);
      wg_wait<0>();
      fence_regs(oa); fence_regs(ob);
      XSTAMP(27);
      release(8); release(0);
      pack16(o1, oa); pack16(o1 + 16, ob);
      float oc[32];
      pv(oc, pa, 2, 0);
      wg_commit();
      XSTAMP(28);
      wg_wait<0>();
      fence_regs(oc);
      release(2);
      pack16(o1 + 32, oc);
    }
    TSTAMP(6);
  }
};

__device__ __forceinline__ uint32_t oslot_addr(uint32_t sbase, uint32_t j) { return sbase + oslot(j) * SLOT_BYTES; }
template <bool EARLY, class Mid>
__device__ __forceinline__ void oproj_chunk(float (&a)[32], const uint32_t (&o0)[48], const uint32_t (&o1)[48], int t,
                                            uint32_t d0, uint32_t d1, uint32_t fullo0, int w, uint32_t nxt, Mid mid) {
  auto tsb = [&]() { return fullo0 - FULLO + 512 + w * 128; };
  (void)tsb;
  OSTAMP(0);
  mbar_wait(fullo0 + 8 * t, 0);
  OSTAMP(1);
  if (!EARLY || t != 0 || w != FIRSTW) asm volatile("bar.sync %0, 256;" ::"r"(1 + w) : "memory");
  OSTAMP(2);
  wg_fence();
  if (!EARLY) {
    const uint64_t db = d0 | (0x40000040ull << 32);
#pragma unroll
    for (int j = 0; j < 12; j++)
      wgmma_n64_rs_tb(a, o0[4 * j], o0[4 * j + 1], o0[4 * j + 2], o0[4 * j + 3], db + 128 * j, j != 0);
  }
  {
    const uint64_t db = d1 | (0x40000040ull << 32);
#pragma unroll
    for (int j = 0; j < 12; j++) {
      wgmma_n64_rs_tb(a, o1[4 * j], o1[4 * j + 1], o1[4 * j + 2], o1[4 * j + 3], db + 128 * j, !EARLY || j != 0);
      if (j == (EARLY ? TOKEN_S : TOKEN_AT) && (EARLY || nxt)) asm volatile("bar.arrive %0, 256;" ::"r"(nxt) : "memory");
    }
    wg_commit();
  }
  OSTAMP(3);
  mid();
  OSTAMP(4);
  wg_wait<0>();
  fence_regs(a);
}

__global__ void __cluster_dims__(2, 1, 1) __launch_bounds__(NTHREADS, 1)
fused_kernel(const __grid_constant__ First F, __nv_bfloat16* __restrict__ out, char* part, const __grid_constant__ Params P) {
  extern __shared__ uint8_t smem_raw[];
  const uint32_t sbase = (smem_u32(smem_raw) + 1023u) & ~1023u;
  const uint32_t full0 = sbase + BAR_OFF;
  const uint32_t empty0 = full0 + 72;
  const uint32_t xfull0 = full0 + 144;
  const uint32_t xempty0 = full0 + 168;
  const uint32_t fullo0 = full0 + FULLO;
  const uint32_t emptyo0 = full0 + 400;
  const uint32_t eready = full0 + 344;
  const uint32_t epoch_s = full0 + 352;
  const uint32_t dtab = full0 + 480;
  const uint32_t emptye0 = full0 + EMPTYE;

  const int tid = threadIdx.x, lane = tid & 31;
  const int bid = blockIdx.x;
  const int hp = bid & 15, tg = (bid >> 4) & 3, p = bid >> 6;
  const int r = hp & 1;
  const int h0 = hp * HM;
  {
    const int c = tid & 7, rr = tid >> 3;
    const uint32_t d = sbase + rr * 128 + ((c ^ (rr & 7)) << 4);
    const char* gw = F.wqp[p] + (size_t)(rr & 15) * 12288 + (h0 * 3 + (rr >> 4)) * 128 + c * 16;
    const uint32_t dw = sbase + SLOT_BYTES + (rr >> 4) * 8192 + (rr & 15) * 128 + ((c ^ (rr & 7)) << 4);
    const char* gx = F.xp[p] + (size_t)(tg * 192 + rr) * 1280 + c * 16;
    uint32_t d_ = d, dw_ = dw;
    asm volatile("" : "+r"(d_), "+r"(dw_), "+l"(gw), "+l"(gx));
    if (tid < 384) {
#pragma unroll
      for (int i = 0; i < 4; i++) {
        if (i < FS2) asm volatile("cp.async.cg.shared.global [%0], [%1], 16;" ::"r"(dw_ + i * 2048), "l"(gw + i * 196608) : "memory");
        asm volatile("cp.async.cg.shared.global [%0], [%1], 16;" ::"r"(d_ + i * 6144), "l"(gx + i * 61440) : "memory");
      }
      asm volatile("cp.async.commit_group;" ::: "memory");
#pragma unroll
      for (int i = FS2; i < 4; i++)
        asm volatile("cp.async.cg.shared.global [%0], [%1], 16;" ::"r"(dw_ + i * 2048), "l"(gw + i * 196608) : "memory");
      asm volatile("cp.async.commit_group;" ::: "memory");
    }
    else if (tid == TMT) {
      asm volatile("prefetch.tensormap [%0];" ::"l"(&P.x[p]) : "memory");
      asm volatile("prefetch.tensormap [%0];" ::"l"(&P.wq[p]) : "memory");
    }
  }
  const int warp = __shfl_sync(0xffffffffu, tid >> 5, 0);
  auto tsb = [&]() { return full0 + 512 + (warp >> 2) * 128; };
  const int grp = p * 4 + tg;
  const int off = (hp >> 1) + (hp >> 3);
  const bool both = off == 0 || off == 5;
  const bool fin = r == 1 || both;

  if (warp >= 12) {
    asm volatile("setmaxnreg.dec.sync.aligned.u32 32;");
    if (tid == 384) {
#pragma unroll
      for (int i = 2; i < NSLOT; i++) mbar_init(full0 + 8 * i, 1);
      asm volatile("fence.mbarrier_init.release.cluster;" ::: "memory");
    }
    __syncwarp();
    asm volatile("barrier.cluster.arrive.relaxed.aligned;" ::: "memory");
    if (warp == 12) {
      SNOW(sa_);
      if (lane == 0) {
        if (C1) { mbar_arrive(full0 + 16); mbar_arrive(full0 + 24); }
#pragma unroll 1
        for (int c = 1 + C1; c < 5; c++) {
          if (c == FDELAY_C) { const uint32_t t0 = clk32(); while (clk32() - t0 < FDELAY) {} }
          mbar_expect_tx(full0 + 16 * c, SLOT_BYTES);
          tma2d(sbase + 2 * c * SLOT_BYTES, &P.x[p], c * 64, tg * 192, full0 + 16 * c);
          tma2d(sbase + 2 * c * SLOT_BYTES + 12288, &P.x[p], c * 64, tg * 192 + 96, full0 + 16 * c);
          if (c == 4) break;
          mbar_expect_tx(full0 + 8 + 16 * c, SLOT_BYTES);
          tma3d(sbase + (2 * c + 1) * SLOT_BYTES, &P.wq[p], 0, c * 64, h0 * 3, full0 + 8 + 16 * c);
        }
        asm volatile("prefetch.tensormap [%0];" ::"l"(&P.k[p]) : "memory");
        asm volatile("prefetch.tensormap [%0];" ::"l"(&P.v[p]) : "memory");
        asm volatile("prefetch.tensormap [%0];" ::"l"(&P.wo[p]) : "memory");
      }
      SNOW(sb_);
      __syncwarp();
      asm volatile("barrier.cluster.wait.aligned;" ::: "memory");
      if (lane == 0) {
        TSTAMP(3); CSTAMP(28);
        uint32_t slot = 0, phase = 1;
#pragma unroll 1
        for (int i = NSLOT; i < 49; i++) {
          mbar_wait(empty0 + 8 * slot, phase ^ 1);
          mbar_expect_tx(full0 + 8 * slot, SLOT_BYTES);
          do_item(P, i, p, tg, h0, r, sbase + slot * SLOT_BYTES, full0 + 8 * slot);
          if (++slot == NSLOT) { slot = 0; phase ^= 1; }
        }
        TSTAMP(2); CSTAMP(29);
#pragma unroll 1
        for (int e = 0; e < 23; e++) {
          int j;
          uint32_t bar;
          if (e < 11) {
            slot = (uint32_t)(0x20732087654ull >> (4 * e)) & 15u;
            if (e == 8) mbar_wait(emptye0 + 32, 0);
            else mbar_wait(empty0 + 8 * slot, e >= 5 && e < 8);
            if (e >= 4 && e < 7) {
              mbar_expect_tx(full0 + 8 * slot, SLOT_BYTES);
              do_item(P, 45 + e, p, tg, h0, r, sbase + slot * SLOT_BYTES, full0 + 8 * slot);
              continue;
            }
            j = e < 4 ? 4 * e : e - 6 + (e == 10);
          } else {
            const int n = e - 11;
            slot = oslot(n);
            mbar_wait(emptyo0 + 8 * (n >> 1), 0);
            asm volatile("fence.proxy.async.shared::cta;" ::: "memory");
            j = n + 6 + (n >= 2) + (n >= 5);
          }
          bar = e < 4 ? full0 + FULLE + 8 * e : fullo0 + 8 * (j >> 1);
          mbar_expect_tx(bar, SLOT_BYTES);
          tma2d(sbase + slot * SLOT_BYTES, &P.wo[p], chunk_of(index_at(j >> 1, r, both), off) * 64, (h0 + HS * (j & 1)) * 192, bar);
        }
        TSTAMP(1); CSTAMP(30);
        if (fin || RSPLIT) {
          const int lo = RSPLIT && !fin ? 2 * XBUF_BYTES : 0, hi = RSPLIT && !both && r ? 2 * XBUF_BYTES : 3 * XBUF_BYTES;
          const char* src = PART + (size_t)(grp * 10 + chunk_of(both ? 8 + r : 9, off)) * 7 * SLOT_BYTES;
          mbar_wait(emptyo0 + 8 * 6, 0);
          asm volatile("fence.proxy.async.shared::cta;" ::: "memory");
          mbar_expect_tx(fullo0 + 8 * 14, 2 * (hi - lo));
          TSTAMP(4);
          bulk_g2s(oslot_addr(sbase, 12) + lo, src + lo, hi - lo, fullo0 + 8 * 14);
          bulk_g2s(oslot_addr(sbase, 13) + lo, src + SLOT_BYTES + lo, hi - lo, fullo0 + 8 * 14);
          TSTAMP(5);
          mbar_wait(emptyo0 + 8 * 7, 0);
          asm volatile("fence.proxy.async.shared::cta;" ::: "memory");
          TSTAMP(6);
#pragma unroll 1
          for (int u = hi - XBUF_BYTES; u >= lo; u -= XBUF_BYTES) {
            const uint32_t bar = fullo0 + 8 * 16 + (u >> 10);
            mbar_expect_tx(bar, 2 * XBUF_BYTES);
            bulk_g2s(oslot_addr(sbase, 14) + u, src + 2 * SLOT_BYTES + u, XBUF_BYTES, bar);
            bulk_g2s(oslot_addr(sbase, 15) + u, src + 3 * SLOT_BYTES + u, XBUF_BYTES, bar);
          }
          TSTAMP(7);
        }
      }
    } else {
      const int w = warp - 13;
      unsigned epoch;
      asm volatile("ld.global.cg.u32 %0, [%1];" : "=r"(epoch) : "l"(part + PART_BYTES + 4 * grp));
      {
        uint32_t sink = sbase + SINK_OFF + (w * 20 + lane) * 16;
        int un = 0;
        uint32_t rot = 0;
        asm volatile("barrier.cluster.wait.aligned;" ::: "memory");
        if (PFE > 1) mbar_wait(full0 + 8 * PFE, 0);
        if (PFE_D) { const uint32_t t0 = clk32(); while (clk32() - t0 < PFE_D) __nanosleep(32); }
        if (lane < 16)
          asm volatile("cp.async.cg.shared.global.L2::128B [%0], [%1], 16;" ::"r"(sink + (PF_DEPTH - 1) * 960),
                       "l"(P.wqp[p] + (size_t)(lane * 4 + tg) * 12288 + h0 * 384 + w * 128 + 4 * 786432) : "memory");
        asm volatile("cp.async.commit_group;" ::: "memory");
        mbar_wait(full0 + 8 * PF_TRIG, 0);
        uint32_t due = clk32();
#pragma unroll 1
        for (int ph = PF0 ? -1 : 0; ph < 5; ph++) {
          const char* q;
          int nb = 4, nt = 3, nl = 16;
          uint32_t sb = 589824;
          if (ph == 1 || ph < 0) {
            q = P.wqp[p] + (size_t)(lane * 4 + tg) * 12288 + (h0 + HS * (ph > 0)) * 384 + w * 128;
            nb = 10; nt = 1; sb = 786432;
            if (ph < 0) {
              nl = 20;
              if (lane >= 16) { q = P.xp[p] + (size_t)(tg * 192 + hp * 12 + w * 4 + lane - 16) * 1280; sb = 128; }
              nb = 10 - PF0_FROM; q += PF0_FROM * sb;
            }
          } else {
            q = (ph < 3 ? P.kp[p] : P.vp[p]) + (size_t)(tg * 128 + h0 + HS * (ph == 2 || ph == 4)) * 18432 + (w * 16 + lane) * 128;
          }
#pragma unroll 1
          for (int b = 0; b < nb; b++, q += sb) {
            if (ph > 0 && mbar_test(emptye0 + 32, 0)) break;
#pragma unroll 1
            for (int t = 0; t < nt; t++) {
              if (ph < 0) asm volatile("cp.async.wait_group %0;" ::"n"(PF_WIN0 - 1) : "memory");
              else if (ph < PF_NW) asm volatile("cp.async.wait_group %0;" ::"n"(PF_WIN1 - 1) : "memory");
              else asm volatile("cp.async.wait_group %0;" ::"n"(PF_WIN - 1) : "memory");
              if (PACE) {
                while ((int)(clk32() - due) < 0) __nanosleep(32);
                due += ph >= PH2 ? PACE2 : PACE;
              }
              if (!(un & 1)) { PSTAMP(un >> 1); }
              if (lane < nl)
                asm volatile("cp.async.cg.shared.global.L2::128B [%0], [%1], 16;" ::"r"(sink + rot), "l"(q + t * 6144) : "memory");
              asm volatile("cp.async.commit_group;" ::: "memory");
              un++;
              rot = rot == (PF_DEPTH - 1) * 960 ? 0 : rot + 960;
            }
          }
          if (ph == 0) {
            if (lane < 5) {
              const int ci = 2 * lane + r, c = chunk_of(ci, off);
              asm volatile("st.shared.u32 [%0], %1;" ::"r"(dtab + 4 * lane), "r"(((grp * 10 + c) * 7 + pos_of(ci, c)) * SLOT_BYTES) : "memory");
            }
            __syncwarp();
            if (lane == 0) {
              asm volatile("st.shared.u32 [%0], %1;" ::"r"(epoch_s), "r"(epoch) : "memory");
              mbar_arrive(eready);
            }
          }
        }
#pragma unroll 1
        for (int n = WOPF0; n < WOPF; n++) {
          const int j = n + 6 - (n < -1) + (n >= 2) + (n >= 5);
          const char* q = P.wop[p] + (size_t)((h0 + HS * (j & 1)) * 192 + tg * 48 + w * 16 + lane) * 1280 + chunk_of(index_at(j >> 1, r, both), off) * 128;
          asm volatile("cp.async.wait_group %0;" ::"n"(PF_WIN - 1) : "memory");
          while ((int)(clk32() - due) < 0) __nanosleep(32);
          due = clk32() + WOPACE;
          if (lane < 16)
            asm volatile("cp.async.cg.shared.global.L2::128B [%0], [%1], 16;" ::"r"(sink + rot), "l"(q) : "memory");
          asm volatile("cp.async.commit_group;" ::: "memory");
          rot = rot == (PF_DEPTH - 1) * 960 ? 0 : rot + 960;
        }
        asm volatile("cp.async.wait_all;" ::: "memory");
      }
    }
    __syncwarp();
    TDUMP();
  } else {
    SNOW(se_);
    if (tid == 128) {
      mbar_init(full0, 1); mbar_init(full0 + 8, 1);
      for (int i = 0; i < NSLOT; i++) mbar_init(empty0 + 8 * i, 24);
      for (int i = 0; i < 3; i++) { mbar_init(xfull0 + 8 * i, 1); mbar_init(xempty0 + 8 * i, 4); }
      for (int i = 0; i < 9; i++) mbar_init(emptyo0 + 8 * i, 12);
      mbar_init(eready, 3);
      for (int i = 0; i < 5; i++) mbar_init(emptye0 + 8 * i, 12);
      for (int i = 0; i < 19; i++) mbar_init(fullo0 + 8 * i, 1 + ((0x3aau >> i) & 1));
      asm volatile("fence.mbarrier_init.release.cluster;" ::: "memory");
      for (int i = 0; i < 3; i++) mbar_expect_tx(xfull0 + 8 * i, XBUF_BYTES);
      mbar_arrive(full0); mbar_arrive(full0 + 8);
    }
    __syncwarp();
    asm volatile("barrier.cluster.arrive.relaxed.aligned;" ::: "memory");
    asm volatile("setmaxnreg.inc.sync.aligned.u32 160;");
    SNOW(sd_);
    asm volatile("barrier.cluster.wait.aligned;" ::: "memory");
    asm volatile("cp.async.wait_group %0;" ::"n"(1 + C1) : "memory");
    asm volatile("fence.proxy.async.shared::cta;" ::: "memory");
    asm volatile("bar.sync 4, 384;" ::: "memory");
    const int w = warp >> 2;
    const int hf = warp / 3 - w;
    uint32_t o0[48], o1[48];
    const uint32_t never = (out == nullptr);
    {
      Front f{{0, 0}, sbase, full0, mapa(empty0, lane & 1), never, w, lane, hf};
      f.run(o0, o1);
    }
#pragma unroll
    for (int i = 0; i < 12; i++) o0[i] ^= never;
    fence_regs(o0); fence_regs(o1);

    const int wt = tid & 127;
    uint32_t tok = w == 0 ? TOK0 : w == 1 ? TOK1 : TOK2;
    const bool finw = RSPLIT ? both || (r == 1) != (w == 2) : fin;
    if (RSPLIT && !fin) tok = w == 0 ? 0xfaaabu : w == 1 ? TOK1 : 0x2555au;
    const uint32_t xb = sbase + XBUF_OFF + w * XBUF_BYTES + wt * 16;
    mbar_wait(eready, 0);
    uint32_t tag;
    asm volatile("ld.shared.u32 %0, [%1];" : "=r"(tag) : "r"(epoch_s) : "memory");
    tag = __shfl_sync(0xffffffffu, ~tag & 1u, 0);
    float a[32];
    uint32_t x[16];
    const uint32_t toff = w * XBUF_BYTES + wt * 16;
    uint4* dst;
    auto publish = [&]() {
#pragma unroll
      for (int j = 0; j < 4; j++)
        asm volatile("st.relaxed.gpu.global.v4.b32 [%0], {%1, %2, %3, %4};"
                     ::"l"(dst + j * 128), "r"(x[4 * j]), "r"(x[4 * j + 1]), "r"(x[4 * j + 2]), "r"(x[4 * j + 3]) : "memory");
    };
    const uint32_t dbase = ((sbase & 0x3FFFFu) >> 4) | 0x10000u;
    uint64_t tbl = OSLOTS;
    uint32_t d0 = dbase + ((uint32_t)OSLOTS & 7u) * (SLOT_BYTES / 16), d1 = dbase + ((uint32_t)(OSLOTS >> 3) & 7u) * (SLOT_BYTES / 16);
    auto mkdst = [&](int k) {
      uint32_t u;
      asm volatile("ld.shared.u32 %0, [%1];" : "=r"(u) : "r"(dtab + 4 * k) : "memory");
      dst = reinterpret_cast<uint4*>(PART + (u + toff));
      asm volatile("" : "+l"(dst));
    };
    auto prepare = [&](int t, bool early) {
      const int ci = index_at(t, r, both);
      const int k = early ? t >> 1 : (ci >> 1) + (RSPLIT && t == 9 && r);
      if (early || (ci & 1) != r || t == 9) {
        if (k == 0) mbar_wait(empty0 + 8 * 8, 1);
        else mbar_wait(xempty0 + 8 * w, (k - 1) & 1);
        if (early) {
          load_tile(x, sbase + ((d0 - dbase) << 4) + toff);
          mkdst(k);
        }
      } else {
        RSTAMP(0);
        mbar_wait(xfull0 + 8 * w, k & 1);
        RSTAMP(1);
        load_tile(x, xb);
        if (k < 4 || finw) {
          if (wt == 0) mbar_expect_tx(xfull0 + 8 * w, XBUF_BYTES);
          __syncwarp();
          if (lane == 0) mbar_arrive_cluster(mapa(xempty0 + 8 * w, r ^ 1) + ((x[0] | x[4] | x[8] | x[12]) & never));
        }
        if (k == 4) mkdst(4);
      }
      tbl >>= 6;
      tok >>= 2;
      d0 = dbase + ((uint32_t)tbl & 7u) * (SLOT_BYTES / 16);
      d1 = dbase + (((uint32_t)tbl >> 3) & 7u) * (SLOT_BYTES / 16);
      fence_regs(x);
    };
    auto epilogue = [&](int t, bool early) {
      const int ci = index_at(t, r, both);
      uint32_t z[16];
#pragma unroll
      for (int j = 0; j < 16; j++) z[j] = pack_bf16(a[2 * j], a[2 * j + 1]);
      if (early || (ci & 1) != r || t == 9) {
        const uint32_t rxb = mapa(xb, r ^ 1);
        const uint32_t rbar = mapa(xfull0 + 8 * w, r ^ 1);
        if (early) {
#pragma unroll
          for (int j = 0; j < 16; j++) z[j] = add_bf16x2(z[j], x[j]);
          fence_regs(z);
        }
        if (lane == 0 && t < 9) mbar_arrive(emptyo0 + 8 * t);
#pragma unroll
        for (int j = 0; j < 4; j++)
          asm volatile("st.async.weak.shared::cluster.mbarrier::complete_tx::bytes.v4.b32 [%0], {%1, %2, %3, %4}, [%5];"
                       ::"r"(rxb + j * 2048), "r"(z[4 * j]), "r"(z[4 * j + 1]), "r"(z[4 * j + 2]), "r"(z[4 * j + 3]), "r"(rbar) : "memory");
      } else {
        if (lane == 0) mbar_arrive(emptyo0 + 8 * t);
#pragma unroll
        for (int j = 0; j < 16; j++) x[j] = add_bf16x2(z[j], x[j]);
#pragma unroll
        for (int j = 0; j < 16; j += 4) x[j] = (x[j] & ~1u) | tag;
        fence_regs(x);
        publish();
      }
      ESTAMP(20 + t);
    };
    auto finalize = [&]() {
      const int c = chunk_of(both ? 8 + r : 9, off);
      TSTAMP(7);
      const uint4* tiles = reinterpret_cast<const uint4*>(PART) + (size_t)(grp * 10 + c) * 7 * (SLOT_BYTES / 16) + w * 512 + wt;
      auto load_g = [&](uint32_t (&y)[16], int q) {
#pragma unroll
        for (int j = 0; j < 4; j++)
          asm volatile("ld.relaxed.gpu.global.v4.b32 {%0, %1, %2, %3}, [%4];"
                       : "=r"(y[4 * j]), "=r"(y[4 * j + 1]), "=r"(y[4 * j + 2]), "=r"(y[4 * j + 3])
                       : "l"(tiles + q * (SLOT_BYTES / 16) + j * 128) : "memory");
      };
      const uint32_t tm = tag - 1u;
      const uint32_t t0 = clk32();
      auto settle = [&](uint32_t (&y)[16], int q) {
        while (true) {
          if (tile_ok(y, tm) || clk32() - t0 > SPIN_LIMIT) break;
          load_g(y, q);
        }
        add_tile(a, y);

      };
      uint32_t e0[16], k4 = 0u;
      if (Y0P < 3) load_g(e0, 4);
      mbar_wait(fullo0 + 8 * 14, 0);
      uint32_t ok = 1u;
#pragma unroll
      for (int h = 0; h < NPRE; h++) {
        if (h) {
          fence_regs(x);
          mbar_wait(fullo0 + 8 * (16 + w), 0);
        }
#pragma unroll
        for (int j = 0; j < 4; j++) {
          uint32_t y[2][4];
#pragma unroll
          for (int q = 0; q < 2; q++)
            asm volatile("ld.shared.v4.b32 {%0, %1, %2, %3}, [%4];"
                         : "=r"(y[q][0]), "=r"(y[q][1]), "=r"(y[q][2]), "=r"(y[q][3])
                         : "r"(oslot_addr(sbase, 12 + 2 * h + q) + toff + j * 2048) : "memory");
          ok &= lop3<0x42>(y[0][0], y[1][0], tm);
#pragma unroll
          for (int i = 0; i < 4; i++) {
            const uint32_t u = add_bf16x2(y[0][i], y[1][i]);
            if (!h) {
              x[4 * j + i] = u;
            } else {
              const uint32_t s = add_bf16x2(x[4 * j + i], u);
              a[8 * j + 2 * i] = __uint_as_float(s << 16);
              a[8 * j + 2 * i + 1] = __uint_as_float(s & 0xffff0000u);
            }
          }
        }
      }
      if (!ok) {
#pragma unroll
        for (int j = 0; j < 32; j++) a[j] = 0.f;
        k4 = 0u;
#pragma unroll 1
        for (int q = 0; q < 4; q++) {
          uint32_t x[16];
          load_g(x, q);
          settle(x, q);
        }
      }
      fence_regs(a);
      ZSTAMP(30);
      load_g(e0, 4);
      mbar_wait(fullo0 + 8 * 9, 0);
      asm volatile("bar.sync %0, 256;" ::"r"(1 + w) : "memory");
      wg_fence();
      {
        const uint64_t db = make_desc(oslot_addr(sbase, 18), 16, 1024);
#pragma unroll
        for (int j = 0; j < 12; j++) wgmma_n64_rs_tb(a, o0[4 * j], o0[4 * j + 1], o0[4 * j + 2], o0[4 * j + 3], db + 128 * j, 1);
        wg_commit();
      }
      {
        const uint64_t db = make_desc(oslot_addr(sbase, 19), 16, 1024);
#pragma unroll
        for (int j = 0; j < 12; j++) {
          wgmma_n64_rs_tb(a, o1[4 * j], o1[4 * j + 1], o1[4 * j + 2], o1[4 * j + 3], db + 128 * j, 1);
          if (j == TOKEN_AT && tok) asm volatile("bar.arrive %0, 256;" ::"r"(tok) : "memory");
        }
        wg_commit();
      }
      {
        uint32_t x[16], y0[16], y1[16], y2[16];
        wg_wait<1>();
        load_g(y2, 6);
        if (!G5) load_g(y1, 5);
#pragma unroll
        for (int j = 0; j < 16; j++) y0[j] = e0[j];
        wg_wait<0>();
        fence_regs(a);
        TSTAMP(19);
        while (true) {
          const uint32_t k0 = tile_ok(y0, tm), k1 = tile_ok(y1, tm), k2 = tile_ok(y2, tm);
          if ((k0 & k1 & k2) || clk32() - t0 > SPIN_LIMIT) break;
          if (!k0) load_g(y0, 4);
          if (!k1) load_g(y1, 5);
          if (!k2) load_g(y2, 6);
        }
#pragma unroll
        for (int j = 0; j < 16; j++) y0[j] = add_bf16x2(add_bf16x2(y0[j], y1[j]), y2[j]);
        add_tile(a, y0);
        fence_regs(a);
        ZSTAMP(31);
        mbar_wait(xfull0 + 8 * w, !fin); load_tile(x, xb);
        add_tile(a, x);
      }
      TSTAMP(8);
      const int row = tg * 192 + w * 64 + (wt >> 5) * 16 + ((wt >> 2) & 7);
      uint4* d0 = reinterpret_cast<uint4*>(out + (size_t)row * 1280 + p * 640 + c * 64 + (wt & 3) * 8);
      const bool b0 = wt & 1, b1 = wt & 2;
      __syncwarp();
#pragma unroll
      for (int u = 0; u < 4; u++) {
        uint32_t x[4];
#pragma unroll
        for (int i = 0; i < 4; i++) {
          const int j = (u & 1) * 4 + i;
          x[i] = pack_bf16(a[4 * j + (u >> 1) * 2], a[4 * j + (u >> 1) * 2 + 1]);
        }
        uint32_t v;
        v = __shfl_xor_sync(0xffffffffu, b0 ? x[0] : x[1], 1); if (b0) x[0] = v; else x[1] = v;
        v = __shfl_xor_sync(0xffffffffu, b0 ? x[2] : x[3], 1); if (b0) x[2] = v; else x[3] = v;
        v = __shfl_xor_sync(0xffffffffu, b1 ? x[0] : x[2], 2); if (b1) x[0] = v; else x[2] = v;
        v = __shfl_xor_sync(0xffffffffu, b1 ? x[1] : x[3], 2); if (b1) x[1] = v; else x[3] = v;
        d0[(u & 1) * 4 + (u >> 1) * 8 * 160] = make_uint4(x[0], x[1], x[2], x[3]);
      }
      if (hp == 1 && tid == 0) asm volatile("red.relaxed.gpu.global.add.u32 [%0], 1;" ::"l"(part + PART_BYTES + 4 * grp) : "memory");
    };
#pragma unroll 1
    for (int t = 0; t < 10; t++) {
      if (t < 8 && !(t & 1)) {
        oproj_chunk<true>(a, o0, o1, t, d0, d1, fullo0, w, tok & 3u, [&]() { prepare(t, true); });
        TSTAMP(10 + t);
        epilogue(t, true);
        t++;
      }
      if (t == 9 && finw) { finalize(); break; }
      oproj_chunk<false>(a, o0, o1, t, d0, d1, fullo0, w, tok & 3u, [&]() { prepare(t, false); });
      TSTAMP(10 + t);
      epilogue(t, false);
    }
    TSTAMP(9);
    __syncwarp();
    TDUMP();
  }
}

typedef CUresult (*EncodeFn)(CUtensorMap*, CUtensorMapDataType, cuuint32_t, void*, const cuuint64_t*, const cuuint64_t*,
                             const cuuint32_t*, const cuuint32_t*, CUtensorMapInterleave, CUtensorMapSwizzle,
                             CUtensorMapL2promotion, CUtensorMapFloatOOBfill);

static void encode(EncodeFn fn, CUtensorMap* m, const void* ptr, int rank, const cuuint64_t* dims, const cuuint64_t* strides,
                   const cuuint32_t* box, int promo) {
  cuuint32_t es[5] = {1, 1, 1, 1, 1};
  fn(m, CU_TENSOR_MAP_DATA_TYPE_BFLOAT16, (cuuint32_t)rank, const_cast<void*>(ptr), dims, strides, box, es,
     CU_TENSOR_MAP_INTERLEAVE_NONE, CU_TENSOR_MAP_SWIZZLE_128B, (CUtensorMapL2promotion)promo,
     CU_TENSOR_MAP_FLOAT_OOB_FILL_NONE);
}
#define PR_X 3
#define PR_WQ 2
#define PR_K 3
#define PR_V 3
#define PR_WO 2

}

extern "C" void kernel_launch(void* const* d_in, const int* in_sizes, int n_in, void* d_out, int out_size) {
  using namespace fk;
  static Params params;
  static const void* cached[10] = {nullptr};
  static EncodeFn fn = nullptr;
  static char* part = nullptr;
  if (!fn) {
    void* f = nullptr;
    cudaDriverEntryPointQueryResult st;
    cudaGetDriverEntryPoint("cuTensorMapEncodeTiled", &f, cudaEnableDefault, &st);
    fn = (EncodeFn)f;
    void* e = nullptr;
    cudaGetSymbolAddress(&e, g_part);
    part = (char*)e;
    cudaFuncSetAttribute(fused_kernel, cudaFuncAttributeMaxDynamicSharedMemorySize, SMEM_BYTES);
  }
  bool same = true;
  for (int i = 0; i < 10; i++) same = same && (cached[i] == d_in[i]);
  if (!same) {
    for (int p = 0; p < 2; p++) {
      const void* x = d_in[5 * p + 0];
      const void* k = d_in[5 * p + 1];
      const void* v = d_in[5 * p + 2];
      const void* wq = d_in[5 * p + 3];
      const void* wo = d_in[5 * p + 4];
      params.kp[p] = (const char*)k; params.vp[p] = (const char*)v;
      params.wqp[p] = (const char*)wq; params.xp[p] = (const char*)x; params.wop[p] = (const char*)wo;
      {
        cuuint64_t d[2] = {640, 768}, s[1] = {1280};
        cuuint32_t b[2] = {64, 96};
        encode(fn, &params.x[p], x, 2, d, s, b, PR_X);
      }
      {
        cuuint64_t d[3] = {64, 640, 96}, s[2] = {12288, 128};
        cuuint32_t b[3] = {64, 64, 3};
        encode(fn, &params.wq[p], wq, 3, d, s, b, PR_WQ);
      }
      {
        cuuint64_t d[4] = {192, 48, 32, 16}, s[3] = {384, 18432, 589824};
        cuuint32_t b[4] = {64, 48, 1, 4};
        encode(fn, &params.k[p], k, 4, d, s, b, PR_K);
        encode(fn, &params.v[p], v, 4, d, s, b, PR_V);
      }
      {
        cuuint64_t d[2] = {640, 6144}, s[1] = {1280};
        cuuint32_t b[2] = {64, 192};
        encode(fn, &params.wo[p], wo, 2, d, s, b, PR_WO);
      }
    }
    for (int i = 0; i < 10; i++) cached[i] = d_in[i];
  }
  const First first = {{params.wqp[0], params.wqp[1]}, {params.xp[0], params.xp[1]}};
  fused_kernel<<<128, NTHREADS, SMEM_BYTES>>>(first, (__nv_bfloat16*)d_out, part, params);
}
```
